```python
import torch

def _softmax(x, axis=-1):
    return torch.softmax(x, dim=axis)
def _gelu(x):
    return torch.nn.functional.gelu(x, approximate="tanh")
def _silu(x):
    return torch.nn.functional.silu(x)
def _sigmoid(x):
    return torch.sigmoid(x)
def _layernorm(x, axis=-1, eps=1e-5):
    m = x.mean(dim=axis, keepdim=True)
    v = x.var(dim=axis, keepdim=True, unbiased=False)
    return (x - m) / torch.sqrt(v + eps)
def _scatter_add(tgt, idx, src, axis=0):
    return tgt.clone().index_add_(axis, idx, src)
def _segment_sum(src, seg, n):
    out = torch.zeros((n,) + src.shape[1:], dtype=src.dtype)
    return out.index_add_(0, seg, src)
def _pad(x, pw):
    flat = tuple(v for pair in reversed(pw) for v in pair)
    return torch.nn.functional.pad(x, flat)

kernel_name = 'interleave_layers__mha_block__dense_activation_silu__prompt'

def setup_inputs():

    _w = (lambda a: (lambda t: t.to(torch.bfloat16) if t.is_floating_point() else t)(torch.as_tensor(a)))
    def _A_setup():
        B, S, D, H = 1, 2048, 640, 32
        return {
            "x": _w((lambda *s: torch.randn(*s, dtype=torch.bfloat16) * 0.05)(B, S, D)),
            "wqkv": _w((lambda *s: torch.randn(*s, dtype=torch.bfloat16) * 0.05)(D, 3 * D)),
            "wo": _w((lambda *s: torch.randn(*s, dtype=torch.bfloat16) * 0.05)(D, D)),
        }
    _A_in = _A_setup()

    def _B_setup():
        B, S, D, F = 1, 2048, 640, 1728
        return {
            "x": _w((lambda *s: torch.randn(*s, dtype=torch.bfloat16) * 0.05)(B, S, D)),
            "w1": _w((lambda *s: torch.randn(*s, dtype=torch.bfloat16) * 0.8)(D, F) * (D ** -0.5)),
            "w2": _w((lambda *s: torch.randn(*s, dtype=torch.bfloat16) * 0.8)(F, D) * (F ** -0.5)),
        }
    _B_in = _B_setup()

    return {
        "A_x": _A_in["x"],
        "A_wqkv": _A_in["wqkv"],
        "A_wo": _A_in["wo"],
        "B_x": _B_in["x"],
        "B_w1": _B_in["w1"],
        "B_w2": _B_in["w2"],
    }

def reference(A_x, A_wqkv, A_wo, B_x, B_w1, B_w2):
    def _A_ref(x, wqkv, wo):
        B, S, D = x.shape
        H = 32
        Dh = D // H
        qkv = (lambda x, *d: x.permute(*d))((x @ wqkv).reshape(B, S, 3, H, Dh), 2, 0, 3, 1, 4)
        q, k, v = qkv[0], qkv[1], qkv[2]
        scores = torch.einsum("bhqd,bhkd->bhqk", q, k) * (Dh ** -0.5)
        p = _softmax(scores, axis=-1)
        o = torch.einsum("bhqk,bhkd->bhqd", p, v)
        return (lambda x, *d: x.permute(*d))(o, 0, 2, 1, 3).reshape(B, S, D) @ wo

    def _B_ref(x, w1, w2):
        h = torch.einsum("bsd,df->bsf", x, w1)
        h = _silu(h)
        out = torch.einsum("bsf,fd->bsd", h, w2)
        return out

    x = A_x
    x = x + _A_ref(_layernorm(x, axis=-1), A_wqkv, A_wo)
    x = x + _B_ref(_layernorm(x, axis=-1), B_w1, B_w2)
    x = x + _A_ref(_layernorm(x, axis=-1), A_wqkv, A_wo)
    x = x + _B_ref(_layernorm(x, axis=-1), B_w1, B_w2)
    return x
```

```cpp
#include <cuda_runtime.h>
#include <cuda_bf16.h>
#include <cuda_fp16.h>
#include <cuda.h>
#include <stdint.h>

__device__ __forceinline__ uint32_t smem_u32(const void* p) { return (uint32_t)__cvta_generic_to_shared(p); }
__device__ __forceinline__ void mbar_init(uint32_t a, uint32_t c) { asm volatile("mbarrier.init.shared::cta.b64 [%0], %1;" :: "r"(a), "r"(c) : "memory"); }
__device__ __forceinline__ void mbar_expect_tx(uint32_t a, uint32_t b) { asm volatile("mbarrier.arrive.expect_tx.shared::cta.b64 _, [%0], %1;" :: "r"(a), "r"(b) : "memory"); }
__device__ __forceinline__ void mbar_arrive(uint32_t a) { asm volatile("mbarrier.arrive.shared::cta.b64 _, [%0];" :: "r"(a) : "memory"); }
__device__ __forceinline__ void mbar_arrive_cluster(uint32_t a, uint32_t cta) {
    asm volatile("{\n.reg .b32 r;\nmapa.shared::cluster.u32 r, %0, %1;\nmbarrier.arrive.shared::cluster.b64 _, [r];\n}" :: "r"(a), "r"(cta) : "memory");
}
__device__ __forceinline__ bool mbar_try(uint32_t a, uint32_t ph) {
    uint32_t ok;
    asm volatile("{\n.reg .pred p;\nmbarrier.try_wait.parity.shared::cta.b64 p, [%1], %2;\nselp.u32 %0,1,0,p;\n}" : "=r"(ok) : "r"(a), "r"(ph) : "memory");
    return ok;
}
__device__ __forceinline__ bool mbar_test(uint32_t a, uint32_t ph) {
    uint32_t ok;
    asm volatile("{\n.reg .pred p;\nmbarrier.test_wait.parity.shared::cta.b64 p, [%1], %2;\nselp.u32 %0,1,0,p;\n}" : "=r"(ok) : "r"(a), "r"(ph) : "memory");
    return ok;
}
__device__ __forceinline__ void mbar_wait(uint32_t a, uint32_t ph) {
    if (mbar_try(a, ph)) return;
    const long long t0 = clock64();
    while (!mbar_try(a, ph)) { if (clock64() - t0 > (1ll << 27)) __trap(); }
}
__device__ __forceinline__ void bulk_g2s(uint32_t dst, const void* src, uint32_t sz, uint32_t bar) {
    asm volatile("cp.async.bulk.shared::cluster.global.mbarrier::complete_tx::bytes [%0], [%1], %2, [%3];" :: "r"(dst), "l"(src), "r"(sz), "r"(bar) : "memory");
}
__device__ __forceinline__ void bulk_s2g(void* dst, uint32_t src, uint32_t sz) {
    asm volatile("cp.async.bulk.global.shared::cta.bulk_group [%0], [%1], %2;" :: "l"(dst), "r"(src), "r"(sz) : "memory");
}
__device__ __forceinline__ void bulk_commit() { asm volatile("cp.async.bulk.commit_group;" ::: "memory"); }
__device__ __forceinline__ void bulk_wait_all() { asm volatile("cp.async.bulk.wait_group 0;" ::: "memory"); }
__device__ __forceinline__ void bulk_wait_read() { asm volatile("cp.async.bulk.wait_group.read 0;" ::: "memory"); }
__device__ __forceinline__ void fence_async_smem() { asm volatile("fence.proxy.async.shared::cta;" ::: "memory"); }
__device__ __forceinline__ void pdl_wait() { asm volatile("griddepcontrol.wait;" ::: "memory"); }
__device__ __forceinline__ void pdl_launch() { asm volatile("griddepcontrol.launch_dependents;" ::: "memory"); }
__device__ __forceinline__ void wg_fence() { asm volatile("wgmma.fence.sync.aligned;" ::: "memory"); }
__device__ __forceinline__ void wg_commit() { asm volatile("wgmma.commit_group.sync.aligned;" ::: "memory"); }
template <int N> __device__ __forceinline__ void wg_wait() { asm volatile("wgmma.wait_group.sync.aligned %0;" :: "n"(N) : "memory"); }
template <int N> __device__ __forceinline__ void fence_regs(float (&r)[N]) {
#pragma unroll
    for (int i = 0; i < N; i++) asm volatile("" : "+f"(r[i]) :: "memory");
}
template <int N> __device__ __forceinline__ void fence_regs(uint32_t (&r)[N]) {
#pragma unroll
    for (int i = 0; i < N; i++) asm volatile("" : "+r"(r[i]) :: "memory");
}
__device__ __forceinline__ bool elect_one() {
    uint32_t p; asm volatile("{\n.reg .pred p;\nelect.sync _|p, 0xffffffff;\nselp.u32 %0,1,0,p;\n}" : "=r"(p)); return p;
}
__device__ __forceinline__ uint64_t mk_desc(uint32_t addr, uint32_t lbo, uint32_t sbo, uint32_t sw) {
    return (uint64_t)((addr & 0x3FFFF) >> 4) | ((uint64_t)(lbo >> 4) << 16) | ((uint64_t)(sbo >> 4) << 32) | ((uint64_t)sw << 62);
}
__device__ __forceinline__ void named_bar_sync(int id, int n) { asm volatile("bar.sync %0, %1;" :: "r"(id), "r"(n) : "memory"); }
__device__ __forceinline__ bool named_bar_or(int id, int n, bool pred) {
    uint32_t r;
    asm volatile("{\n.reg .pred p, q;\nsetp.ne.u32 q, %3, 0;\nbar.red.or.pred p, %1, %2, q;\nselp.u32 %0,1,0,p;\n}" : "=r"(r) : "r"(id), "r"(n), "r"((uint32_t)pred) : "memory");
    return r;
}
__device__ __forceinline__ float ex2f(float x) { float y; asm("ex2.approx.ftz.f32 %0, %1;" : "=f"(y) : "f"(x)); return y; }
__device__ __forceinline__ uint32_t pack_f16(float lo, float hi) { uint32_t d; asm("cvt.rn.f16x2.f32 %0, %1, %2;" : "=r"(d) : "f"(hi), "f"(lo)); return d; }
__device__ __forceinline__ uint32_t pack_bf16(float lo, float hi) { uint32_t d; asm("cvt.rn.bf16x2.f32 %0, %1, %2;" : "=r"(d) : "f"(hi), "f"(lo)); return d; }
__device__ __forceinline__ uint32_t hfma2(uint32_t a, uint32_t b, uint32_t c) { uint32_t d; asm("fma.rn.f16x2 %0, %1, %2, %3;" : "=r"(d) : "r"(a), "r"(b), "r"(c)); return d; }

__device__ __forceinline__ void red_release_add(unsigned* p, unsigned v) { asm volatile("red.release.gpu.global.add.u32 [%0], %1;" :: "l"(p), "r"(v) : "memory"); }
__device__ __forceinline__ void flag_wait(const unsigned* p, unsigned target, unsigned mask = 0xFFFFFFFFu) {
    uint32_t n = 0, v;
    while (true) {
        asm volatile("ld.acquire.gpu.global.u32 %0, [%1];" : "=r"(v) : "l"(p) : "memory");
        if ((v & mask) >= target) break;
        if (++n > (1u << 17)) __trap();
    }
}
__device__ __forceinline__ void tma_3d(uint32_t dst, const CUtensorMap* m, int c0, int c1, int c2, uint32_t bar) {
    asm volatile("cp.async.bulk.tensor.3d.shared::cluster.global.mbarrier::complete_tx::bytes [%0], [%1, {%3, %4, %5}], [%2];"
                 :: "r"(dst), "l"(m), "r"(bar), "r"(c0), "r"(c1), "r"(c2) : "memory");
}
constexpr int CNT_STRIDE = 64, CNT_LN = 0, CNT_CS = 16 * CNT_STRIDE, CNT_RETILE = 24 * CNT_STRIDE, CNT_FLAGS = 25 * CNT_STRIDE;
constexpr int CNT_TOTAL = CNT_FLAGS + 2 * 96 * CNT_STRIDE;
constexpr unsigned RETILE_UNITS = 940;

__device__ __forceinline__ void wgmma_n128_bf16_rs_tb0(float (&d)[64], uint32_t a0, uint32_t a1, uint32_t a2, uint32_t a3, uint64_t db) {
  asm volatile("wgmma.mma_async.sync.aligned.m64n128k16.f32.bf16.bf16 {%0, %1, %2, %3, %4, %5, %6, %7, %8, %9, %10, %11, %12, %13, %14, %15, %16, %17, %18, %19, %20, %21, %22, %23, %24, %25, %26, %27, %28, %29, %30, %31, %32, %33, %34, %35, %36, %37, %38, %39, %40, %41, %42, %43, %44, %45, %46, %47, %48, %49, %50, %51, %52, %53, %54, %55, %56, %57, %58, %59, %60, %61, %62, %63}, {%64, %65, %66, %67}, %68, 1, 1, 1, 0;"
  : "+f"(d[0]), "+f"(d[1]), "+f"(d[2]), "+f"(d[3]), "+f"(d[4]), "+f"(d[5]), "+f"(d[6]), "+f"(d[7]), "+f"(d[8]), "+f"(d[9]), "+f"(d[10]), "+f"(d[11]), "+f"(d[12]), "+f"(d[13]), "+f"(d[14]), "+f"(d[15]), "+f"(d[16]), "+f"(d[17]), "+f"(d[18]), "+f"(d[19]), "+f"(d[20]), "+f"(d[21]), "+f"(d[22]), "+f"(d[23]), "+f"(d[24]), "+f"(d[25]), "+f"(d[26]), "+f"(d[27]), "+f"(d[28]), "+f"(d[29]), "+f"(d[30]), "+f"(d[31]), "+f"(d[32]), "+f"(d[33]), "+f"(d[34]), "+f"(d[35]), "+f"(d[36]), "+f"(d[37]), "+f"(d[38]), "+f"(d[39]), "+f"(d[40]), "+f"(d[41]), "+f"(d[42]), "+f"(d[43]), "+f"(d[44]), "+f"(d[45]), "+f"(d[46]), "+f"(d[47]), "+f"(d[48]), "+f"(d[49]), "+f"(d[50]), "+f"(d[51]), "+f"(d[52]), "+f"(d[53]), "+f"(d[54]), "+f"(d[55]), "+f"(d[56]), "+f"(d[57]), "+f"(d[58]), "+f"(d[59]), "+f"(d[60]), "+f"(d[61]), "+f"(d[62]), "+f"(d[63])
  : "r"(a0), "r"(a1), "r"(a2), "r"(a3), "l"(db));
}
__device__ __forceinline__ void wgmma_n128_bf16_rs_tb0_init(float (&d)[64], uint32_t a0, uint32_t a1, uint32_t a2, uint32_t a3, uint64_t db) {
  asm volatile("wgmma.mma_async.sync.aligned.m64n128k16.f32.bf16.bf16 {%0, %1, %2, %3, %4, %5, %6, %7, %8, %9, %10, %11, %12, %13, %14, %15, %16, %17, %18, %19, %20, %21, %22, %23, %24, %25, %26, %27, %28, %29, %30, %31, %32, %33, %34, %35, %36, %37, %38, %39, %40, %41, %42, %43, %44, %45, %46, %47, %48, %49, %50, %51, %52, %53, %54, %55, %56, %57, %58, %59, %60, %61, %62, %63}, {%64, %65, %66, %67}, %68, 0, 1, 1, 0;"
  : "=f"(d[0]), "=f"(d[1]), "=f"(d[2]), "=f"(d[3]), "=f"(d[4]), "=f"(d[5]), "=f"(d[6]), "=f"(d[7]), "=f"(d[8]), "=f"(d[9]), "=f"(d[10]), "=f"(d[11]), "=f"(d[12]), "=f"(d[13]), "=f"(d[14]), "=f"(d[15]), "=f"(d[16]), "=f"(d[17]), "=f"(d[18]), "=f"(d[19]), "=f"(d[20]), "=f"(d[21]), "=f"(d[22]), "=f"(d[23]), "=f"(d[24]), "=f"(d[25]), "=f"(d[26]), "=f"(d[27]), "=f"(d[28]), "=f"(d[29]), "=f"(d[30]), "=f"(d[31]), "=f"(d[32]), "=f"(d[33]), "=f"(d[34]), "=f"(d[35]), "=f"(d[36]), "=f"(d[37]), "=f"(d[38]), "=f"(d[39]), "=f"(d[40]), "=f"(d[41]), "=f"(d[42]), "=f"(d[43]), "=f"(d[44]), "=f"(d[45]), "=f"(d[46]), "=f"(d[47]), "=f"(d[48]), "=f"(d[49]), "=f"(d[50]), "=f"(d[51]), "=f"(d[52]), "=f"(d[53]), "=f"(d[54]), "=f"(d[55]), "=f"(d[56]), "=f"(d[57]), "=f"(d[58]), "=f"(d[59]), "=f"(d[60]), "=f"(d[61]), "=f"(d[62]), "=f"(d[63])
  : "r"(a0), "r"(a1), "r"(a2), "r"(a3), "l"(db));
}
__device__ __forceinline__ void wgmma_n64_bf16_rs_tb0(float (&d)[32], uint32_t a0, uint32_t a1, uint32_t a2, uint32_t a3, uint64_t db) {
  asm volatile("wgmma.mma_async.sync.aligned.m64n64k16.f32.bf16.bf16 {%0, %1, %2, %3, %4, %5, %6, %7, %8, %9, %10, %11, %12, %13, %14, %15, %16, %17, %18, %19, %20, %21, %22, %23, %24, %25, %26, %27, %28, %29, %30, %31}, {%32, %33, %34, %35}, %36, 1, 1, 1, 0;"
  : "+f"(d[0]), "+f"(d[1]), "+f"(d[2]), "+f"(d[3]), "+f"(d[4]), "+f"(d[5]), "+f"(d[6]), "+f"(d[7]), "+f"(d[8]), "+f"(d[9]), "+f"(d[10]), "+f"(d[11]), "+f"(d[12]), "+f"(d[13]), "+f"(d[14]), "+f"(d[15]), "+f"(d[16]), "+f"(d[17]), "+f"(d[18]), "+f"(d[19]), "+f"(d[20]), "+f"(d[21]), "+f"(d[22]), "+f"(d[23]), "+f"(d[24]), "+f"(d[25]), "+f"(d[26]), "+f"(d[27]), "+f"(d[28]), "+f"(d[29]), "+f"(d[30]), "+f"(d[31])
  : "r"(a0), "r"(a1), "r"(a2), "r"(a3), "l"(db));
}
__device__ __forceinline__ void wgmma_n64_bf16_rs_tb0_init(float (&d)[32], uint32_t a0, uint32_t a1, uint32_t a2, uint32_t a3, uint64_t db) {
  asm volatile("wgmma.mma_async.sync.aligned.m64n64k16.f32.bf16.bf16 {%0, %1, %2, %3, %4, %5, %6, %7, %8, %9, %10, %11, %12, %13, %14, %15, %16, %17, %18, %19, %20, %21, %22, %23, %24, %25, %26, %27, %28, %29, %30, %31}, {%32, %33, %34, %35}, %36, 0, 1, 1, 0;"
  : "=f"(d[0]), "=f"(d[1]), "=f"(d[2]), "=f"(d[3]), "=f"(d[4]), "=f"(d[5]), "=f"(d[6]), "=f"(d[7]), "=f"(d[8]), "=f"(d[9]), "=f"(d[10]), "=f"(d[11]), "=f"(d[12]), "=f"(d[13]), "=f"(d[14]), "=f"(d[15]), "=f"(d[16]), "=f"(d[17]), "=f"(d[18]), "=f"(d[19]), "=f"(d[20]), "=f"(d[21]), "=f"(d[22]), "=f"(d[23]), "=f"(d[24]), "=f"(d[25]), "=f"(d[26]), "=f"(d[27]), "=f"(d[28]), "=f"(d[29]), "=f"(d[30]), "=f"(d[31])
  : "r"(a0), "r"(a1), "r"(a2), "r"(a3), "l"(db));
}
__device__ __forceinline__ void wgmma_n24_f16_rs_tb1(float (&d)[12], uint32_t a0, uint32_t a1, uint32_t a2, uint32_t a3, uint64_t db) {
  asm volatile("wgmma.mma_async.sync.aligned.m64n24k16.f32.f16.f16 {%0, %1, %2, %3, %4, %5, %6, %7, %8, %9, %10, %11}, {%12, %13, %14, %15}, %16, 1, 1, 1, 1;"
  : "+f"(d[0]), "+f"(d[1]), "+f"(d[2]), "+f"(d[3]), "+f"(d[4]), "+f"(d[5]), "+f"(d[6]), "+f"(d[7]), "+f"(d[8]), "+f"(d[9]), "+f"(d[10]), "+f"(d[11])
  : "r"(a0), "r"(a1), "r"(a2), "r"(a3), "l"(db));
}
__device__ __forceinline__ void wgmma_n240_bf16_ss_tb1(float (&d)[120], uint64_t da, uint64_t db) {
  asm volatile("wgmma.mma_async.sync.aligned.m64n240k16.f32.bf16.bf16 {%0, %1, %2, %3, %4, %5, %6, %7, %8, %9, %10, %11, %12, %13, %14, %15, %16, %17, %18, %19, %20, %21, %22, %23, %24, %25, %26, %27, %28, %29, %30, %31, %32, %33, %34, %35, %36, %37, %38, %39, %40, %41, %42, %43, %44, %45, %46, %47, %48, %49, %50, %51, %52, %53, %54, %55, %56, %57, %58, %59, %60, %61, %62, %63, %64, %65, %66, %67, %68, %69, %70, %71, %72, %73, %74, %75, %76, %77, %78, %79, %80, %81, %82, %83, %84, %85, %86, %87, %88, %89, %90, %91, %92, %93, %94, %95, %96, %97, %98, %99, %100, %101, %102, %103, %104, %105, %106, %107, %108, %109, %110, %111, %112, %113, %114, %115, %116, %117, %118, %119}, %120, %121, 1, 1, 1, 0, 1;"
  : "+f"(d[0]), "+f"(d[1]), "+f"(d[2]), "+f"(d[3]), "+f"(d[4]), "+f"(d[5]), "+f"(d[6]), "+f"(d[7]), "+f"(d[8]), "+f"(d[9]), "+f"(d[10]), "+f"(d[11]), "+f"(d[12]), "+f"(d[13]), "+f"(d[14]), "+f"(d[15]), "+f"(d[16]), "+f"(d[17]), "+f"(d[18]), "+f"(d[19]), "+f"(d[20]), "+f"(d[21]), "+f"(d[22]), "+f"(d[23]), "+f"(d[24]), "+f"(d[25]), "+f"(d[26]), "+f"(d[27]), "+f"(d[28]), "+f"(d[29]), "+f"(d[30]), "+f"(d[31]), "+f"(d[32]), "+f"(d[33]), "+f"(d[34]), "+f"(d[35]), "+f"(d[36]), "+f"(d[37]), "+f"(d[38]), "+f"(d[39]), "+f"(d[40]), "+f"(d[41]), "+f"(d[42]), "+f"(d[43]), "+f"(d[44]), "+f"(d[45]), "+f"(d[46]), "+f"(d[47]), "+f"(d[48]), "+f"(d[49]), "+f"(d[50]), "+f"(d[51]), "+f"(d[52]), "+f"(d[53]), "+f"(d[54]), "+f"(d[55]), "+f"(d[56]), "+f"(d[57]), "+f"(d[58]), "+f"(d[59]), "+f"(d[60]), "+f"(d[61]), "+f"(d[62]), "+f"(d[63]), "+f"(d[64]), "+f"(d[65]), "+f"(d[66]), "+f"(d[67]), "+f"(d[68]), "+f"(d[69]), "+f"(d[70]), "+f"(d[71]), "+f"(d[72]), "+f"(d[73]), "+f"(d[74]), "+f"(d[75]), "+f"(d[76]), "+f"(d[77]), "+f"(d[78]), "+f"(d[79]), "+f"(d[80]), "+f"(d[81]), "+f"(d[82]), "+f"(d[83]), "+f"(d[84]), "+f"(d[85]), "+f"(d[86]), "+f"(d[87]), "+f"(d[88]), "+f"(d[89]), "+f"(d[90]), "+f"(d[91]), "+f"(d[92]), "+f"(d[93]), "+f"(d[94]), "+f"(d[95]), "+f"(d[96]), "+f"(d[97]), "+f"(d[98]), "+f"(d[99]), "+f"(d[100]), "+f"(d[101]), "+f"(d[102]), "+f"(d[103]), "+f"(d[104]), "+f"(d[105]), "+f"(d[106]), "+f"(d[107]), "+f"(d[108]), "+f"(d[109]), "+f"(d[110]), "+f"(d[111]), "+f"(d[112]), "+f"(d[113]), "+f"(d[114]), "+f"(d[115]), "+f"(d[116]), "+f"(d[117]), "+f"(d[118]), "+f"(d[119])
  : "l"(da), "l"(db));
}
__device__ __forceinline__ void wgmma_n216_bf16_ss_tb1(float (&d)[108], uint64_t da, uint64_t db) {
  asm volatile("wgmma.mma_async.sync.aligned.m64n216k16.f32.bf16.bf16 {%0, %1, %2, %3, %4, %5, %6, %7, %8, %9, %10, %11, %12, %13, %14, %15, %16, %17, %18, %19, %20, %21, %22, %23, %24, %25, %26, %27, %28, %29, %30, %31, %32, %33, %34, %35, %36, %37, %38, %39, %40, %41, %42, %43, %44, %45, %46, %47, %48, %49, %50, %51, %52, %53, %54, %55, %56, %57, %58, %59, %60, %61, %62, %63, %64, %65, %66, %67, %68, %69, %70, %71, %72, %73, %74, %75, %76, %77, %78, %79, %80, %81, %82, %83, %84, %85, %86, %87, %88, %89, %90, %91, %92, %93, %94, %95, %96, %97, %98, %99, %100, %101, %102, %103, %104, %105, %106, %107}, %108, %109, 1, 1, 1, 0, 1;"
  : "+f"(d[0]), "+f"(d[1]), "+f"(d[2]), "+f"(d[3]), "+f"(d[4]), "+f"(d[5]), "+f"(d[6]), "+f"(d[7]), "+f"(d[8]), "+f"(d[9]), "+f"(d[10]), "+f"(d[11]), "+f"(d[12]), "+f"(d[13]), "+f"(d[14]), "+f"(d[15]), "+f"(d[16]), "+f"(d[17]), "+f"(d[18]), "+f"(d[19]), "+f"(d[20]), "+f"(d[21]), "+f"(d[22]), "+f"(d[23]), "+f"(d[24]), "+f"(d[25]), "+f"(d[26]), "+f"(d[27]), "+f"(d[28]), "+f"(d[29]), "+f"(d[30]), "+f"(d[31]), "+f"(d[32]), "+f"(d[33]), "+f"(d[34]), "+f"(d[35]), "+f"(d[36]), "+f"(d[37]), "+f"(d[38]), "+f"(d[39]), "+f"(d[40]), "+f"(d[41]), "+f"(d[42]), "+f"(d[43]), "+f"(d[44]), "+f"(d[45]), "+f"(d[46]), "+f"(d[47]), "+f"(d[48]), "+f"(d[49]), "+f"(d[50]), "+f"(d[51]), "+f"(d[52]), "+f"(d[53]), "+f"(d[54]), "+f"(d[55]), "+f"(d[56]), "+f"(d[57]), "+f"(d[58]), "+f"(d[59]), "+f"(d[60]), "+f"(d[61]), "+f"(d[62]), "+f"(d[63]), "+f"(d[64]), "+f"(d[65]), "+f"(d[66]), "+f"(d[67]), "+f"(d[68]), "+f"(d[69]), "+f"(d[70]), "+f"(d[71]), "+f"(d[72]), "+f"(d[73]), "+f"(d[74]), "+f"(d[75]), "+f"(d[76]), "+f"(d[77]), "+f"(d[78]), "+f"(d[79]), "+f"(d[80]), "+f"(d[81]), "+f"(d[82]), "+f"(d[83]), "+f"(d[84]), "+f"(d[85]), "+f"(d[86]), "+f"(d[87]), "+f"(d[88]), "+f"(d[89]), "+f"(d[90]), "+f"(d[91]), "+f"(d[92]), "+f"(d[93]), "+f"(d[94]), "+f"(d[95]), "+f"(d[96]), "+f"(d[97]), "+f"(d[98]), "+f"(d[99]), "+f"(d[100]), "+f"(d[101]), "+f"(d[102]), "+f"(d[103]), "+f"(d[104]), "+f"(d[105]), "+f"(d[106]), "+f"(d[107])
  : "l"(da), "l"(db));
}
__device__ __forceinline__ void wgmma_n80_bf16_ss_tb1(float (&d)[40], uint64_t da, uint64_t db) {
  asm volatile("wgmma.mma_async.sync.aligned.m64n80k16.f32.bf16.bf16 {%0, %1, %2, %3, %4, %5, %6, %7, %8, %9, %10, %11, %12, %13, %14, %15, %16, %17, %18, %19, %20, %21, %22, %23, %24, %25, %26, %27, %28, %29, %30, %31, %32, %33, %34, %35, %36, %37, %38, %39}, %40, %41, 1, 1, 1, 0, 1;"
  : "+f"(d[0]), "+f"(d[1]), "+f"(d[2]), "+f"(d[3]), "+f"(d[4]), "+f"(d[5]), "+f"(d[6]), "+f"(d[7]), "+f"(d[8]), "+f"(d[9]), "+f"(d[10]), "+f"(d[11]), "+f"(d[12]), "+f"(d[13]), "+f"(d[14]), "+f"(d[15]), "+f"(d[16]), "+f"(d[17]), "+f"(d[18]), "+f"(d[19]), "+f"(d[20]), "+f"(d[21]), "+f"(d[22]), "+f"(d[23]), "+f"(d[24]), "+f"(d[25]), "+f"(d[26]), "+f"(d[27]), "+f"(d[28]), "+f"(d[29]), "+f"(d[30]), "+f"(d[31]), "+f"(d[32]), "+f"(d[33]), "+f"(d[34]), "+f"(d[35]), "+f"(d[36]), "+f"(d[37]), "+f"(d[38]), "+f"(d[39])
  : "l"(da), "l"(db));
}
__device__ __forceinline__ void wgmma_n24_f16acc_rs_tb1(uint32_t (&d)[6], uint32_t a0, uint32_t a1, uint32_t a2, uint32_t a3, uint64_t db, int sd) {
  asm volatile("{\n.reg .pred p;\nsetp.ne.b32 p, %11, 0;\n"
  "wgmma.mma_async.sync.aligned.m64n24k16.f16.f16.f16 {%0, %1, %2, %3, %4, %5}, {%6, %7, %8, %9}, %10, p, 1, 1, 1;\n}\n"
  : "+r"(d[0]), "+r"(d[1]), "+r"(d[2]), "+r"(d[3]), "+r"(d[4]), "+r"(d[5])
  : "r"(a0), "r"(a1), "r"(a2), "r"(a3), "l"(db), "r"(sd));
}

constexpr int SEQ = 2048, DM = 640, NH = 32, DH = 20, FF = 1728;
constexpr int HEAD_IMG = 256 * 384;
#define PV 2
#define MMASK 0x4949
constexpr uint32_t MUFU_MASK = MMASK;
#define IS_MUFU(b) ((MUFU_MASK >> ((b) & 15)) & 1)
#define TWO_M70 8.4703294725430034e-22f
#define TWO_M69 1.6940658945086007e-21f
#define TWO_P70 1.1805916207174113e+21f
#define TWO_P100 1.2676506002282294e+30f
#define TWO_P39 549755813888.0f
#define TWO_M100 7.8886090522101181e-31f
#define TWO_M39 1.8189894035458565e-12f

__device__ __forceinline__ uint32_t exp_pair_mufu(float a, float b) { return pack_f16(ex2f(a), ex2f(b)); }
__device__ __forceinline__ uint32_t exp_pair_poly(float a, float b, uint32_t c3c, uint32_t ctop) {
    uint32_t v, g, q, p;
    asm("cvt.pack.sat.s16.s32 %0, %1, %2;" : "=r"(v) : "r"(__float_as_uint(b)), "r"(__float_as_uint(a)));
    asm("lop3.b32 %0, %1, 0x03FF03FF, %2, 0xEA;" : "=r"(g) : "r"(v), "r"(c3c));
    q = hfma2(g, ctop, 0xA434A434u);
    q = hfma2(q, g, 0x39743974u);
    asm("lop3.b32 %0, %1, %2, 0x03FF03FF, 0xD8;" : "=r"(p) : "r"(v), "r"(q));
    return p;
}
__device__ __forceinline__ uint32_t attn_mslot(float mt, int t) {
    const float m = -mt * TWO_M70;
    const uint32_t hi = __float_as_uint(m) & 0xFFFF0000u;
    const float r = m - __uint_as_float(hi);
    const uint32_t mid = __float_as_uint(r) & 0xFFFF0000u;
    const uint32_t lo = __float_as_uint(r - __uint_as_float(mid));
    return (t == 2) ? ((hi >> 16) | mid) : ((lo >> 16) | 0x1C800000u);
}

template <int NB>
__device__ __forceinline__ float attn_rowmax(const float (&s)[4 * NB], int r) {
    float mm = -INFINITY, mp = -INFINITY;
#pragma unroll
    for (int b = 0; b < NB; b++) {
        const float m2 = fmaxf(s[4 * b + 2 * r], s[4 * b + 2 * r + 1]);
        if (IS_MUFU(b)) mm = fmaxf(mm, m2); else mp = fmaxf(mp, m2);
    }
    float mx = fmaxf(mm, (mp * TWO_P100) * TWO_P39 - 15.0f);
    mx = fmaxf(mx, __shfl_xor_sync(0xffffffffu, mx, 1));
    return fmaxf(mx, __shfl_xor_sync(0xffffffffu, mx, 2));
}

struct AttnConst { uint32_t c3c, ctop; int t; };

template <bool SAFE>
__device__ __forceinline__ void attn_tile(float (&o)[12], uint32_t (&oh)[6], int acc, uint32_t (&q)[8], float (&mt)[2], uint64_t dK, uint64_t dK2, uint64_t dV, const AttnConst& c) {
    float s[64];
    wg_fence();
    wgmma_n128_bf16_rs_tb0_init(s, q[0], q[1], q[2], q[3], dK);
    wgmma_n128_bf16_rs_tb0(s, q[4], q[5], q[6], q[7], dK2);
    wg_commit();
    wg_wait<0>();
    fence_regs(s);
    if (SAFE) {
#pragma unroll
        for (int r = 0; r < 2; r++) {
            const float d = fmaxf(ceilf(attn_rowmax<16>(s, r)) - 10.0f, 0.0f);
            const float dp = (d * TWO_M100) * TWO_M39;
#pragma unroll
            for (int b = 0; b < 16; b++) {
                const float dd = IS_MUFU(b) ? d : dp;
                s[4 * b + 2 * r] -= dd; s[4 * b + 2 * r + 1] -= dd;
            }
            const float sc = ex2f(-d);
#pragma unroll
            for (int b = 0; b < 3; b++) { o[4 * b + 2 * r] *= sc; o[4 * b + 2 * r + 1] *= sc; }
            mt[r] += d;
            const uint32_t ms = attn_mslot(mt[r], c.t);
            if (c.t >= 2) q[4 + r] = ms;
        }
    }
    uint32_t p[32];
#pragma unroll
    for (int h = 0; h < 4; h++) {
#pragma unroll
        for (int b = 4 * h; b < 4 * h + 4; b++) {
            if (IS_MUFU(b)) {
                p[2 * b] = exp_pair_mufu(s[4 * b], s[4 * b + 1]);
                p[2 * b + 1] = exp_pair_mufu(s[4 * b + 2], s[4 * b + 3]);
            } else {
                p[2 * b] = exp_pair_poly(s[4 * b], s[4 * b + 1], c.c3c, c.ctop);
                p[2 * b + 1] = exp_pair_poly(s[4 * b + 2], s[4 * b + 3], c.c3c, c.ctop);
            }
        }
        wg_fence();
#pragma unroll
        for (int kk = 2 * h; kk < 2 * h + 2; kk++) {
            if (SAFE) wgmma_n24_f16_rs_tb1(o, p[4 * kk], p[4 * kk + 1], p[4 * kk + 2], p[4 * kk + 3], dV + kk * 48);
            else wgmma_n24_f16acc_rs_tb1(oh, p[4 * kk], p[4 * kk + 1], p[4 * kk + 2], p[4 * kk + 3], dV + kk * 48, kk == 0 ? acc : 1);
        }
    }
    wg_commit();
    wg_wait<0>();
    if (SAFE) fence_regs(o); else fence_regs(oh);
}

constexpr int ATTN_SMEM = 2 * HEAD_IMG + 4 * 8192 + 256;

struct RetileArgs { uint8_t* dst; unsigned* cnt; int enable; };
__device__ __noinline__ void retile_step(int st, int wg, uint32_t base, const CUtensorMap* maps, uint8_t* dst, unsigned* cnt) {
    const uint32_t buf = base + (wg & 1) * 16384, bar = base + 4 * 8192 + 48 + 8 * (wg & 1), barfree = bar + 16;
    const int u0 = wg * 256 + blockIdx.x * 2;
    const bool on = u0 < (int)RETILE_UNITS;
    if (st == 0) {
        if (wg >= 2) mbar_wait(barfree, 0);
        if (on) {
            mbar_expect_tx(bar, 2 * 8192);
#pragma unroll
            for (int j = 0; j < 2; j++) {
                int u = u0 + j, m, kb, cg;
                if (u < 100) { m = 0; kb = u / 10; cg = u - kb * 10; }
                else if (u < 370) { m = 1; u -= 100; kb = u / 27; cg = u - kb * 27; }
                else if (u < 640) { m = 2; u -= 370; kb = u / 10; cg = u - kb * 10; }
                else { m = 3; u -= 640; kb = u / 30; cg = u - kb * 30; }
                tma_3d(buf + j * 8192, maps + m, 0, kb * 64, cg * 8, bar);
            }
        }
    } else if (st == 1) {
        if (on) {
            mbar_wait(bar, wg >> 1);
            bulk_s2g(dst + (size_t)u0 * 8192, buf, 2 * 8192);
            bulk_commit();
        }
    } else {
        bulk_wait_all();
        if (wg < 2) { mbar_arrive(barfree); red_release_add(cnt + CNT_RETILE, 1); }
    }
}
struct RetileMaps { CUtensorMap m[4]; };
constexpr int ATTN_THREADS = 512;

__global__ void __launch_bounds__(ATTN_THREADS, 1) attn_kernel(const uint8_t* __restrict__ qkv, __nv_bfloat16* __restrict__ out, const float* __restrict__ vinv,
                                                               const __grid_constant__ RetileMaps rmaps, const RetileArgs rargs, int kid) {
    extern __shared__ __align__(1024) uint8_t smem[];
    const uint32_t sK = smem_u32(smem), sV = sK + HEAD_IMG;
    const uint32_t bars = sK + 2 * HEAD_IMG + 4 * 8192;
    const float* s_vi = reinterpret_cast<const float*>(smem + 2 * HEAD_IMG + 4 * 8192 + 128);
    const int tid = threadIdx.x, head = blockIdx.x >> 2, qb = blockIdx.x & 3;
    if (tid == 0) {
#pragma unroll
        for (int c = 0; c < 10; c++) mbar_init(bars + 8 * c, 1);
        asm volatile("fence.mbarrier_init.release.cluster;" ::: "memory");
    }
    __syncthreads();
    const int wid = __shfl_sync(0xffffffffu, tid >> 5, 0);
    const bool rt = rargs.enable && (tid & 127) == 96;
    if (rargs.enable && tid < 4) asm volatile("prefetch.tensormap [%0];" :: "l"(&rmaps.m[tid]) : "memory");
    pdl_wait();
    if (rargs.enable && blockIdx.x == 0 && tid < 24) rargs.cnt[CNT_LN + tid * CNT_STRIDE] = 0;
    if (wid == 15) {
        if (elect_one()) {
            const uint8_t* gK = qkv + (size_t)(NH + head) * HEAD_IMG;
            const uint8_t* gV = qkv + (size_t)(2 * NH + head) * HEAD_IMG;
            mbar_expect_tx(bars, 2 * 6144); bulk_g2s(sK, gK, 2 * 6144, bars);
            mbar_expect_tx(bars + 8, 2 * 6144); bulk_g2s(sV, gV, 2 * 6144, bars + 8);
            mbar_expect_tx(bars + 16, 8 * 6144); bulk_g2s(sK + 2 * 6144, gK + 2 * 6144, 4 * 6144, bars + 16); bulk_g2s(sV + 2 * 6144, gV + 2 * 6144, 4 * 6144, bars + 16);
            mbar_expect_tx(bars + 24, 10 * 6144); bulk_g2s(sK + 6 * 6144, gK + 6 * 6144, 5 * 6144, bars + 24); bulk_g2s(sV + 6 * 6144, gV + 6 * 6144, 5 * 6144, bars + 24);
            mbar_expect_tx(bars + 32, 10 * 6144 + 80); bulk_g2s(sK + 11 * 6144, gK + 11 * 6144, 5 * 6144, bars + 32); bulk_g2s(sV + 11 * 6144, gV + 11 * 6144, 5 * 6144, bars + 32);
            bulk_g2s(bars + 128, vinv + head * DH, 80, bars + 32);
        }
        __syncwarp();
    }
    pdl_launch();
    const int wg = tid >> 7, warp = (tid >> 5) & 3, lane = tid & 31, g = lane >> 2, t = lane & 3;
    const uint64_t dK0 = mk_desc(sK, 128, 384, 0), dK20 = mk_desc(sK + 256, 0, 384, 0), dV0 = mk_desc(sV, 384, 128, 0);
    AttnConst c;
    c.t = t;
    c.c3c = __shfl_sync(0xffffffffu, 0x3C003C00u, 0);
    c.ctop = __shfl_sync(0xffffffffu, 0x35643564u, 0);
    const uint32_t* qp = reinterpret_cast<const uint32_t*>(qkv + (size_t)head * HEAD_IMG + ((qb * 512 + wg * 128 + warp * 16) >> 3) * 384 + lane * 4);
    uint32_t q[8];
    q[0] = __ldcg(qp); q[1] = __ldcg(qp + 96); q[2] = __ldcg(qp + 32); q[3] = __ldcg(qp + 128); q[4] = __ldcg(qp + 64); q[5] = __ldcg(qp + 160);
    if (lane < 6) asm volatile("prefetch.global.L1 [%0];" :: "l"(qp - lane + 768 + 32 * lane));
    q[6] = __shfl_sync(0xffffffffu, lane, 0); q[7] = __shfl_sync(0xffffffffu, lane ^ 1, 1);
    mbar_wait(bars, 0);
    int first = 0;
#pragma unroll 1
    for (int i = 0; i < 2; i++) {
        const int row0 = qb * 512 + (wg * 2 + i) * 64 + warp * 16;
        float o[12], mt[2];
        int attempt = first;
        const int first0 = first;
#pragma unroll 1
        while (true) {
            if (attempt == 0) {
                mt[0] = 4.0f; mt[1] = 4.0f;
                if (t >= 2) { q[4] = (t == 2) ? 0x00009D80u : 0x1C800000u; q[5] = q[4]; }
            } else {
                if (t >= 2) { q[4] = (t == 2) ? 0u : 0x1C800000u; q[5] = q[4]; }
                float s[32];
                wg_fence();
                wgmma_n64_bf16_rs_tb0_init(s, q[0], q[1], q[2], q[3], dK0);
                wgmma_n64_bf16_rs_tb0(s, q[4], q[5], q[6], q[7], dK20);
                wg_commit();
                wg_wait<0>();
                fence_regs(s);
#pragma unroll
                for (int r = 0; r < 2; r++) {
                    mt[r] = ceilf(attn_rowmax<8>(s, r)) - (attempt == 2 ? 10.0f : 4.0f);
                    const uint32_t ms = attn_mslot(mt[r], t);
                    if (t >= 2) q[4 + r] = ms;
                }
            }
#pragma unroll
            for (int k = 0; k < 12; k++) o[k] = 0.0f;
            uint32_t oh[6];
            if (attempt == 2) {
                int j = 0;
#pragma unroll 1
                do { attn_tile<true>(o, oh, 1, q, mt, dK0 + j * 384, dK20 + j * 384, dV0 + j * 384, c); } while (++j < 16);
                break;
            }
            uint32_t j = 0;
#pragma unroll 1
            for (int grp = 0; grp < 4; grp++) {
                const uint32_t j1 = (grp == 0) ? 2 * 384 : (1 + 5 * grp) * 384;
#pragma unroll
                for (int k = 0; k < 6; k++) asm volatile("mov.u32 %0, 0;" : "=r"(oh[k]));
                mbar_wait(bars + 8 + 8 * grp, 0);
#pragma unroll 1
                do { attn_tile<false>(o, oh, 1, q, mt, dK0 + j, dK20 + j, dV0 + j, c); j += 384; } while (j != j1);
#pragma unroll
                for (int k = 0; k < 6; k++) {
                    const float2 f = __half22float2(*reinterpret_cast<const __half2*>(&oh[k]));
                    o[2 * k] += f.x; o[2 * k + 1] += f.y;
                }
                const uint32_t lim = grp ? (5u << 23) : (1u << 23);
                if (__any_sync(0xffffffffu, t >= 2 && (__float_as_uint(o[9]) - ((127u + 5u) << 23) >= lim || __float_as_uint(o[11]) - ((127u + 5u) << 23) >= lim))) {
#pragma unroll
                    for (int r = 0; r < 2; r++) {
                        const uint32_t eb = __shfl_sync(0xffffffffu, __float_as_uint(o[9 + 2 * r]), lane | 2) & 0x7F800000u;
                        const float sc = __uint_as_float(((254u + 5u) << 23) - eb);
#pragma unroll
                        for (int b = 0; b < 3; b++) { o[4 * b + 2 * r] *= sc; o[4 * b + 2 * r + 1] *= sc; }
                        mt[r] += __uint_as_float((eb >> 23) | 0x4B000000u) - (8388608.0f + 127.0f + 5.0f);
                        const uint32_t ms = attn_mslot(mt[r], t);
                        if (t >= 2) q[4 + r] = ms;
                    }
                }
                if (rt && attempt == first0) {
                    const unsigned st = i * 4 + grp - (1 + wg + (wg >> 1));
                    if (st < 3) retile_step(st, wg, sK + 2 * HEAD_IMG, rmaps.m, rargs.dst, rargs.cnt);
                }
                __syncwarp();
            }
            bool bad = !(fabsf(o[9]) < 1e30f && fabsf(o[11]) < 1e30f);
            if (attempt == 0 && t >= 2) bad = bad || !(o[9] * ex2f(mt[0] - 4.0f) >= 8.0f && o[11] * ex2f(mt[1] - 4.0f) >= 8.0f);
            if (!__any_sync(0xffffffffu, named_bar_or(1 + wg, 128, bad))) break;
            attempt++;
            first = 1;
        }
        q[0] = __ldca(qp + 768); q[1] = __ldca(qp + 864); q[2] = __ldca(qp + 800); q[3] = __ldca(qp + 896); q[4] = __ldca(qp + 832); q[5] = __ldca(qp + 928);
        const float2 v0 = *reinterpret_cast<const float2*>(s_vi + 2 * t), v1 = *reinterpret_cast<const float2*>(s_vi + 8 + 2 * t);
        const float2 v2 = *reinterpret_cast<const float2*>(s_vi + 16 + 2 * (t & 1));
#pragma unroll
        for (int r = 0; r < 2; r++) {
            const float il = __fdividef(1.0f, __shfl_sync(0xffffffffu, o[9 + 2 * r], lane | 2));
            uint8_t* op = reinterpret_cast<uint8_t*>(out) + (size_t)(row0 >> 6) * (80 * 1024) + ((row0 & 63) + g + 8 * r) * 16;
            const int c0 = head * DH + 2 * t;
            *reinterpret_cast<uint32_t*>(op + (c0 >> 3) * 1024 + (c0 & 7) * 2) = pack_bf16(o[2 * r] * il * v0.x, o[2 * r + 1] * il * v0.y);
            *reinterpret_cast<uint32_t*>(op + ((c0 >> 3) + 1) * 1024 + (c0 & 7) * 2) = pack_bf16(o[4 + 2 * r] * il * v1.x, o[4 + 2 * r + 1] * il * v1.y);
            if (t < 2) *reinterpret_cast<uint32_t*>(op + ((c0 >> 3) + 2) * 1024 + (c0 & 7) * 2) = pack_bf16(o[8 + 2 * r] * il * v2.x, o[9 + 2 * r] * il * v2.y);
        }
    }
}

__device__ __forceinline__ void tma_2d(uint32_t dst, const CUtensorMap* m, int c0, int c1, uint32_t bar) {
    asm volatile("cp.async.bulk.tensor.2d.shared::cluster.global.mbarrier::complete_tx::bytes [%0], [%1, {%3, %4}], [%2];"
                 :: "r"(dst), "l"(m), "r"(bar), "r"(c0), "r"(c1) : "memory");
}
__device__ __forceinline__ void tma_3d_mc(uint32_t dst, const CUtensorMap* m, int c0, int c1, int c2, uint32_t bar, uint16_t mask) {
    asm volatile("cp.async.bulk.tensor.3d.shared::cluster.global.mbarrier::complete_tx::bytes.multicast::cluster [%0], [%1, {%3, %4, %5}], [%2], %6;"
                 :: "r"(dst), "l"(m), "r"(bar), "r"(c0), "r"(c1), "r"(c2), "h"(mask) : "memory");
}
__device__ __forceinline__ void bulk_g2s_mc(uint32_t dst, const void* src, uint32_t sz, uint32_t bar, uint16_t mask) {
    asm volatile("cp.async.bulk.shared::cluster.global.mbarrier::complete_tx::bytes.multicast::cluster [%0], [%1], %2, [%3], %4;"
                 :: "r"(dst), "l"(src), "r"(sz), "r"(bar), "h"(mask) : "memory");
}
__device__ __forceinline__ void tma_store_2d(const CUtensorMap* m, int c0, int c1, uint32_t src) {
    asm volatile("cp.async.bulk.tensor.2d.global.shared::cta.bulk_group [%0, {%2, %3}], [%1];" :: "l"(m), "r"(src), "r"(c0), "r"(c1) : "memory");
}
__device__ __forceinline__ void prefetch_map(const CUtensorMap* m) { asm volatile("prefetch.tensormap [%0];" :: "l"(m) : "memory"); }
__device__ __forceinline__ void cluster_arrive_relaxed() { asm volatile("barrier.cluster.arrive.relaxed.aligned;" ::: "memory"); }
__device__ __forceinline__ void cluster_wait() { asm volatile("barrier.cluster.wait.acquire.aligned;" ::: "memory"); }
__device__ __forceinline__ float bf_lo(uint32_t v) { return __uint_as_float(v << 16); }
__device__ __forceinline__ float bf_hi(uint32_t v) { return __uint_as_float(v & 0xFFFF0000u); }

__device__ __forceinline__ float2 lds_f2(uint32_t a) { float2 v; asm("ld.shared.v2.f32 {%0, %1}, [%2];" : "=f"(v.x), "=f"(v.y) : "r"(a)); return v; }
__device__ __forceinline__ uint32_t opaque(uint32_t a) { asm volatile("" : "+r"(a) :: "memory"); return a; }

template <int BN> struct Mma;
template <> struct Mma<240> { static __device__ __forceinline__ void run(float (&d)[120], uint64_t a, uint64_t b) { wgmma_n240_bf16_ss_tb1(d, a, b); } };
template <> struct Mma<216> { static __device__ __forceinline__ void run(float (&d)[108], uint64_t a, uint64_t b) { wgmma_n216_bf16_ss_tb1(d, a, b); } };
template <> struct Mma<80>  { static __device__ __forceinline__ void run(float (&d)[40], uint64_t a, uint64_t b) { wgmma_n80_bf16_ss_tb1(d, a, b); } };

__device__ __forceinline__ float2 ln_combine(const float2 (&a)[8]) {
    float s = 0.0f;
#pragma unroll
    for (int j = 0; j < 8; j++) s += a[j].x;
    const float mean = s * (1.0f / 640.0f);
    float m2 = 0.0f;
#pragma unroll
    for (int j = 0; j < 8; j++) { const float d = a[j].x * (1.0f / 80.0f) - mean; m2 += fmaf(80.0f * d, d, a[j].y); }
    return make_float2(mean, rsqrtf(m2 * (1.0f / 640.0f) + 1e-5f));
}

template <int RS, int CS>
__device__ __forceinline__ void res_init(float (&acc)[40], const uint8_t* xw, int rl, int t) {
#pragma unroll
    for (int r = 0; r < 2; r++)
#pragma unroll
        for (int b = 0; b < 10; b++) {
            const uint32_t x = *reinterpret_cast<const uint32_t*>(xw + (rl + 8 * r) * RS + 4 * t + CS * b);
            acc[4 * b + 2 * r] = bf_lo(x); acc[4 * b + 2 * r + 1] = bf_hi(x);
        }
}
template <int RS, int CS>
__device__ __forceinline__ void epi_res(const float (&acc)[40], uint8_t* dst, int rl, int t, uint32_t (&x)[20]) {
#pragma unroll
    for (int r = 0; r < 2; r++)
#pragma unroll
        for (int b = 0; b < 10; b++) {
            x[10 * r + b] = pack_bf16(acc[4 * b + 2 * r], acc[4 * b + 2 * r + 1]);
            *reinterpret_cast<uint32_t*>(dst + (rl + 8 * r) * RS + 4 * t + CS * b) = x[10 * r + b];
        }
}
__device__ __forceinline__ void epi_stats(const uint32_t (&x)[20], int rl, int t, float2* stats) {
    float sum[2], m2[2];
#pragma unroll
    for (int r = 0; r < 2; r++) {
        sum[r] = 0.0f;
#pragma unroll
        for (int b = 0; b < 10; b++) sum[r] += bf_lo(x[10 * r + b]) + bf_hi(x[10 * r + b]);
    }
#pragma unroll
    for (int r = 0; r < 2; r++) { sum[r] += __shfl_xor_sync(0xffffffffu, sum[r], 1); }
#pragma unroll
    for (int r = 0; r < 2; r++) { sum[r] += __shfl_xor_sync(0xffffffffu, sum[r], 2); }
#pragma unroll
    for (int r = 0; r < 2; r++) {
        const float mu = sum[r] * (1.0f / 80.0f);
        float a = 0.0f, b2 = 0.0f;
#pragma unroll
        for (int b = 0; b < 10; b++) { const float d = bf_lo(x[10 * r + b]) - mu, e = bf_hi(x[10 * r + b]) - mu; a = fmaf(d, d, a); b2 = fmaf(e, e, b2); }
        m2[r] = a + b2;
    }
#pragma unroll
    for (int r = 0; r < 2; r++) { m2[r] += __shfl_xor_sync(0xffffffffu, m2[r], 1); }
#pragma unroll
    for (int r = 0; r < 2; r++) { m2[r] += __shfl_xor_sync(0xffffffffu, m2[r], 2); }
    if (t < 2) stats[rl + 8 * t] = t ? make_float2(sum[1], m2[1]) : make_float2(sum[0], m2[0]);
}
__device__ __forceinline__ void epi_res_publish(const float (&acc)[40], uint8_t* xw, float2* s_st, uint8_t* gx, unsigned* flag,
                                                int rl, int t, int warp, int wg) {
    uint32_t x[20];
    epi_res<16, 1024>(acc, xw, rl, t, x);
    fence_async_smem();
    named_bar_sync(1 + wg, 128);
    if (warp == 0 && elect_one()) { bulk_s2g(gx, smem_u32(xw), 10240); bulk_commit(); }
    __syncwarp();
    epi_stats(x, rl, t, s_st);
    asm volatile("bar.arrive %0, 160;" :: "r"(4 + wg) : "memory");
    if (warp == 0 && elect_one()) { bulk_wait_all(); red_release_add(flag, 1); }
    __syncwarp();
}

__device__ __forceinline__ float silu_half(float h) { float t; asm("tanh.approx.f32 %0, %1;" : "=f"(t) : "f"(h)); return fmaf(h, t, h); }

template <int N, int B0, int B1, bool VS>
__device__ __forceinline__ void ln_apply(float (&acc)[N], uint32_t cs, const float2 (&ln)[2], const float (&mul)[2]) {
#pragma unroll
    for (int b = B0; b < B1; b++) {
        const float2 c = lds_f2(cs + 32 * b);
        float2 v = make_float2(1.0f, 1.0f);
        if (VS) v = lds_f2(cs + 960 + 32 * b);
#pragma unroll
        for (int r = 0; r < 2; r++) {
            acc[4 * b + 2 * r] = (VS ? mul[r] * v.x : mul[r]) * fmaf(-ln[r].x, c.x, acc[4 * b + 2 * r]);
            acc[4 * b + 2 * r + 1] = (VS ? mul[r] * v.y : mul[r]) * fmaf(-ln[r].x, c.y, acc[4 * b + 2 * r + 1]);
        }
    }
}

template <int B0, int B1>
__device__ __forceinline__ void epi_silu(const float (&acc)[108], uint8_t* stg, int rl, int t) {
    uint8_t* a0 = stg + rl * 16 + 4 * t;
#pragma unroll
    for (int b = B0; b < B1; b++) {
#pragma unroll
        for (int r = 0; r < 2; r++)
            *reinterpret_cast<uint32_t*>(a0 + r * 128 + 1024 * b) = pack_bf16(silu_half(acc[4 * b + 2 * r]), silu_half(acc[4 * b + 2 * r + 1]));
    }
}

template <int P>
__device__ __forceinline__ void epi_qkv(float (&acc)[120], uint8_t* wbase, const int (&off)[5], uint32_t cs, const float2 (&ln)[2],
                                        const float (&ksc)[2], int type, int t) {
    float mul[2];
#pragma unroll
    for (int r = 0; r < 2; r++) mul[r] = ln[r].y * (type == 0 ? (0.22360679774997896f * 1.4426950408889634f * TWO_M70) : (type == 1 ? ksc[r] : 1.0f));
    const float kc = (t & 1) ? ksc[1] : ksc[0];
    uint2 cst;
    uint32_t pk[10];
    if (type == 2) {
        ln_apply<120, P * 5, P * 5 + 5, true>(acc, cs, ln, mul);
#pragma unroll
        for (int i = 0; i < 10; i++) pk[i] = pack_f16(acc[P * 20 + 2 * i], acc[P * 20 + 2 * i + 1]);
        cst = make_uint2(0x3C003C00u, 0x3C003C00u);
    } else {
        ln_apply<120, P * 5, P * 5 + 5, false>(acc, cs, ln, mul);
#pragma unroll
        for (int i = 0; i < 10; i++) pk[i] = pack_bf16(acc[P * 20 + 2 * i], acc[P * 20 + 2 * i + 1]);
        cst = make_uint2(pack_bf16(kc, kc), pack_bf16(kc, kc < 1.0f ? 15.0f * TWO_M69 : 0.0f));
    }
#pragma unroll
    for (int bb = 0; bb < 5; bb++) {
        uint8_t* a0 = wbase + P * 1536 + off[bb];
        *reinterpret_cast<uint32_t*>(a0) = pk[2 * bb];
        *reinterpret_cast<uint32_t*>(a0 + 384) = pk[2 * bb + 1];
    }
    *reinterpret_cast<uint2*>(wbase + P * 1536 + t * 384 + 264) = cst;
}

__device__ __forceinline__ void epi_qkv_all(float (&acc)[120], uint8_t* stg, const float* cs, const float2 (&ln)[2],
                                            uint8_t* qkv, int nt, int rowblk  , int rl, int t, int warp
    ) {
    const uint32_t sstg = smem_u32(stg) + warp * 9216, csa = opaque(smem_u32(cs) + 8 * t);
    uint8_t* wbase = stg + warp * 9216 + (rl & 7) * 16;
    uint8_t* gdst = qkv + (size_t)nt * 12 * HEAD_IMG + (rowblk + 2 * warp) * 384;
    int off[5];
#pragma unroll
    for (int j = 0; j < 5; j++) { const int col = 8 * j + 2 * t, hl = col >= 20 ? 1 : 0, d = col - hl * 20; off[j] = hl * 768 + (d >> 3) * 128 + (d & 7) * 2; }
    float ksc[2];
#pragma unroll
    for (int r = 0; r < 2; r++) ksc[r] = IS_MUFU(rowblk + 2 * warp + r) ? TWO_P70 : TWO_M69;
#define QKV_PART(P)                                                                                                   \
    epi_qkv<P>(acc, wbase, off, csa, ln, ksc, (nt * 12 + P * 2) >> 5, t);                                             \
    fence_async_smem();                                                                                               \
    __syncwarp();                                                                                                     \
    if (elect_one()) {                                                                                                \
        bulk_s2g(gdst + (size_t)(2 * P) * HEAD_IMG, sstg + P * 1536, 768);                                            \
        bulk_s2g(gdst + (size_t)(2 * P + 1) * HEAD_IMG, sstg + P * 1536 + 768, 768);                                  \
        bulk_commit();                                                                                                \
    }
    QKV_PART(0)
    QKV_PART(1) QKV_PART(2) QKV_PART(3) QKV_PART(4) QKV_PART(5)
#undef QKV_PART
    bulk_wait_read();
}

struct Qkv1Args {
    const __nv_bfloat16 *x, *wqkv, *w1;
    float2* ln0;
    float *cs_qkv, *cs_w1, *vscale, *vinv;
    float *psum, *pmax;
    uint8_t* qkv;
    unsigned* cnt;
    int kid;
};
constexpr int Q1_STAGE = 49152, Q1_STAGES = 4;
constexpr int Q1_SMEM = Q1_STAGES * Q1_STAGE + 128 * 8 + 2 * 240 * 4 + 128 + 128;

__device__ __forceinline__ float v_scale(float m) {
    int e = (int)(__float_as_uint(m) >> 23) - 127 + 1;
    e = e < -100 ? -100 : (e > 100 ? 100 : e);
    return __uint_as_float((uint32_t)(127 - 10 - e) << 23);
}

template <bool MX>
__device__ __forceinline__ void colsum64(const __nv_bfloat16* w, int N, int lane, float* dst, float* dmax) {
    const uint4* p = reinterpret_cast<const uint4*>(w + (size_t)(lane >> 3) * N + (lane & 7) * 8);
    float s[8], m[8];
    uint4 u[20];
#pragma unroll
    for (int i = 0; i < 20; i++) u[i] = __ldg(p + (size_t)i * (N / 2));
#pragma unroll
    for (int j = 0; j < 8; j++) { s[j] = 0.0f; m[j] = 0.0f; }
#pragma unroll
    for (int i = 0; i < 20; i++) {
        const float f[8] = {bf_lo(u[i].x), bf_hi(u[i].x), bf_lo(u[i].y), bf_hi(u[i].y), bf_lo(u[i].z), bf_hi(u[i].z), bf_lo(u[i].w), bf_hi(u[i].w)};
#pragma unroll
        for (int j = 0; j < 8; j++) { s[j] += f[j]; if (MX) m[j] = fmaxf(m[j], fabsf(f[j])); }
    }
#pragma unroll
    for (int o = 8; o < 32; o <<= 1)
#pragma unroll
        for (int j = 0; j < 8; j++) { s[j] += __shfl_xor_sync(0xffffffffu, s[j], o); if (MX) m[j] = fmaxf(m[j], __shfl_xor_sync(0xffffffffu, m[j], o)); }
    if (lane < 8) {
        reinterpret_cast<float4*>(dst)[2 * lane] = make_float4(s[0], s[1], s[2], s[3]);
        reinterpret_cast<float4*>(dst)[2 * lane + 1] = make_float4(s[4], s[5], s[6], s[7]);
        if (MX) {
            reinterpret_cast<float4*>(dmax)[2 * lane] = make_float4(m[0], m[1], m[2], m[3]);
            reinterpret_cast<float4*>(dmax)[2 * lane + 1] = make_float4(m[4], m[5], m[6], m[7]);
        }
    }
}

__global__ void __cluster_dims__(2, 1, 1) __launch_bounds__(384, 1)
qkv1_kernel(const __grid_constant__ CUtensorMap mapA, const __grid_constant__ CUtensorMap mapB, const Qkv1Args args) {
    constexpr int STAGES = Q1_STAGES, STAGE = Q1_STAGE, KB = 10;
    extern __shared__ __align__(1024) uint8_t smem[];
    const uint32_t sbase = smem_u32(smem);
    float2* s_ln = reinterpret_cast<float2*>(smem + STAGES * STAGE);
    float* s_cs = reinterpret_cast<float*>(s_ln + 128);
    float* s_vs = s_cs + 240;
    const uint32_t bfull = smem_u32(s_vs + 240), bempty = bfull + 8 * STAGES;
    float* s_pub = s_vs + 240 + 32;
    const int tid = threadIdx.x, warp = __shfl_sync(0xffffffffu, tid >> 5, 0), lane = tid & 31;
    const uint32_t rank = blockIdx.x & 1;
    const int mt = ((blockIdx.x >> 4) << 1) | (blockIdx.x & 1), nt = (blockIdx.x >> 1) & 7;
    if (tid == 256) { prefetch_map(&mapA); prefetch_map(&mapB); }
    if (warp == 0 && elect_one()) {
#pragma unroll
        for (int s = 0; s < STAGES; s++) { mbar_init(bfull + 8 * s, 1); mbar_init(bempty + 8 * s, 4); }
        asm volatile("fence.mbarrier_init.release.cluster;" ::: "memory");
    }
    __syncwarp();
    cluster_arrive_relaxed();
    cluster_wait();
    pdl_launch();

    if (warp == 8) {
        if (elect_one()) {
            const int rot = ((blockIdx.x >> 4) + nt) % KB;
            int s = 0; uint32_t ph = 1;
#pragma unroll 1
            for (int kb = 0; kb < KB; kb++) {
                if (kb >= STAGES) mbar_wait(bempty + 8 * s, ph);
                const uint32_t sa = sbase + s * STAGE, bar = bfull + 8 * s;
                mbar_expect_tx(bar, STAGE);
                int kr = kb + rot; kr = kr >= KB ? kr - KB : kr;
                tma_2d(sa, &mapA, kr * 64, mt * 128, bar); tma_2d(sa + 8192, &mapA, kr * 64, mt * 128 + 64, bar);
                tma_3d_mc(sa + 16384 + rank * 8192, &mapB, rank * 64, nt, kr * 64, bar, (uint16_t)3);
                tma_3d_mc(sa + 16384 + (2 + rank) * 8192, &mapB, (2 + rank) * 64, nt, kr * 64, bar, (uint16_t)3);
                if (++s == STAGES) { s = 0; ph ^= 1; }
            }
        }
    } else if (warp >= 10) {
        const int hw = warp - 10;
        const int cg = blockIdx.x >> 2, part = (blockIdx.x & 3) * 2 + hw;
        if (cg < 30) {
            const __nv_bfloat16* wp = args.wqkv + (size_t)part * 80 * (3 * DM) + cg * 64;
            if (cg >= 20) colsum64<true>(wp, 3 * DM, lane, args.psum + part * (3 * DM) + cg * 64, args.pmax + part * DM + (cg - 20) * 64);
            else colsum64<false>(wp, 3 * DM, lane, args.psum + part * (3 * DM) + cg * 64, nullptr);
            __syncwarp();
            const int n0 = (64 * cg) / 240, n1 = (64 * cg + 63) / 240;
            if (lane == 0 || (lane == 1 && n1 != n0)) red_release_add(args.cnt + CNT_CS + (lane ? n1 : n0) * CNT_STRIDE, 1);
            __syncwarp();
        }
        if (blockIdx.x == 0 && hw == 0) for (int i = lane; i < 1 + 2 * 96; i += 32) args.cnt[CNT_RETILE + i * CNT_STRIDE] = 0;
        if (cg < 27) colsum64<false>(args.w1 + (size_t)part * 80 * FF + cg * 64, FF, lane, args.cs_w1 + part * FF + cg * 64, nullptr);
    } else if (warp == 9) {
        named_bar_sync(6, 288);
        reinterpret_cast<float*>(args.ln0 + blockIdx.x * 16)[lane] = s_pub[lane];
        __syncwarp();
        if (lane == 0) red_release_add(args.cnt + CNT_LN + (blockIdx.x >> 3) * CNT_STRIDE, 1);
        __syncwarp();
        flag_wait(args.cnt + CNT_LN + mt * CNT_STRIDE, 8);
        float2 l[4];
#pragma unroll
        for (int i = 0; i < 4; i++) l[i] = __ldcg(args.ln0 + mt * 128 + lane + 32 * i);
        flag_wait(args.cnt + CNT_CS + nt * CNT_STRIDE, 8 * ((240 * nt + 239) / 64 - (240 * nt) / 64 + 1));
#pragma unroll
        for (int i = 0; i < 2; i++) {
            const int j = 4 * (lane + 32 * i), col = nt * 240 + j;
            if (j < 240) {
                float4 s = make_float4(0.f, 0.f, 0.f, 0.f), m = s, v = make_float4(1.f, 1.f, 1.f, 1.f);
#pragma unroll
                for (int p = 0; p < 8; p++) {
                    const float4 a = __ldcg(reinterpret_cast<const float4*>(args.psum + p * (3 * DM) + col));
                    s.x += a.x; s.y += a.y; s.z += a.z; s.w += a.w;
                }
                if (col >= 2 * DM) {
#pragma unroll
                    for (int p = 0; p < 8; p++) {
                        const float4 a = __ldcg(reinterpret_cast<const float4*>(args.pmax + p * DM + col - 2 * DM));
                        m.x = fmaxf(m.x, a.x); m.y = fmaxf(m.y, a.y); m.z = fmaxf(m.z, a.z); m.w = fmaxf(m.w, a.w);
                    }
                    v = make_float4(v_scale(m.x), v_scale(m.y), v_scale(m.z), v_scale(m.w));
                    if (mt == 0) {
                        *reinterpret_cast<float4*>(args.vscale + col - 2 * DM) = v;
                        *reinterpret_cast<float4*>(args.vinv + col - 2 * DM) = make_float4(1.0f / v.x, 1.0f / v.y, 1.0f / v.z, 1.0f / v.w);
                    }
                }
                if (mt == 0) *reinterpret_cast<float4*>(args.cs_qkv + col) = s;
                *reinterpret_cast<float4*>(s_cs + j) = s;
                *reinterpret_cast<float4*>(s_vs + j) = v;
            }
        }
#pragma unroll
        for (int i = 0; i < 4; i++) s_ln[lane + 32 * i] = l[i];
        named_bar_sync(3, 288);
    } else {
        const int wg = warp >> 2, g = lane >> 2, t = lane & 3;
        {
            uint2 u[2][5];
            const int r0 = blockIdx.x * 16 + warp * 2;
#pragma unroll
            for (int r = 0; r < 2; r++)
#pragma unroll
                for (int i = 0; i < 5; i++) u[r][i] = __ldg(reinterpret_cast<const uint2*>(args.x + (size_t)(r0 + r) * DM) + lane + 32 * i);
            float sm[2], m2[2];
#pragma unroll
            for (int r = 0; r < 2; r++) {
                sm[r] = 0.0f;
#pragma unroll
                for (int i = 0; i < 5; i++) sm[r] += (bf_lo(u[r][i].x) + bf_hi(u[r][i].x)) + (bf_lo(u[r][i].y) + bf_hi(u[r][i].y));
            }
#pragma unroll
            for (int o = 1; o < 32; o <<= 1) { sm[0] += __shfl_xor_sync(0xffffffffu, sm[0], o); sm[1] += __shfl_xor_sync(0xffffffffu, sm[1], o); }
#pragma unroll
            for (int r = 0; r < 2; r++) {
                const float mean = sm[r] * (1.0f / 640.0f);
                m2[r] = 0.0f;
#pragma unroll
                for (int i = 0; i < 5; i++) {
                    const float a = bf_lo(u[r][i].x) - mean, b = bf_hi(u[r][i].x) - mean, c = bf_lo(u[r][i].y) - mean, d = bf_hi(u[r][i].y) - mean;
                    m2[r] += (a * a + b * b) + (c * c + d * d);
                }
            }
#pragma unroll
            for (int o = 1; o < 32; o <<= 1) { m2[0] += __shfl_xor_sync(0xffffffffu, m2[0], o); m2[1] += __shfl_xor_sync(0xffffffffu, m2[1], o); }
            if (lane < 2) {
                s_pub[(warp * 2 + lane) * 2] = (lane ? sm[1] : sm[0]) * (1.0f / 640.0f);
                s_pub[(warp * 2 + lane) * 2 + 1] = rsqrtf((lane ? m2[1] : m2[0]) * (1.0f / 640.0f) + 1e-5f);
            }
            asm volatile("bar.arrive 6, 288;" ::: "memory");
        }
        float acc[120];
#pragma unroll
        for (int i = 0; i < 120; i++) acc[i] = 0.0f;
        const uint64_t dA0 = mk_desc(sbase + wg * 8192, 16, 1024, 1), dB0 = mk_desc(sbase + 16384, 8192, 1024, 1);
        int s = 0; uint32_t ph = 0;
#pragma unroll 1
        for (int kb = 0; kb < KB; kb++) {
            mbar_wait(bfull + 8 * s, ph);
            const uint64_t dA = dA0 + (uint64_t)(s * (STAGE >> 4)), dB = dB0 + (uint64_t)(s * (STAGE >> 4));
            wg_fence();
#pragma unroll
            for (int k = 0; k < 4; k++) Mma<240>::run(acc, dA + 2 * k, dB + 128 * k);
            wg_commit();
            if (kb > 0) {
                wg_wait<1>();
                const int ps = (s == 0) ? STAGES - 1 : s - 1;
                if (kb - 1 + STAGES < KB && (tid & 127) < 2) mbar_arrive_cluster(bempty + 8 * ps, tid & 1);
            }
            if (++s == STAGES) { s = 0; ph ^= 1; }
        }
        wg_wait<0>();
        named_bar_sync(3, 288);
        const int rl = (warp & 3) * 16 + g;
        const float2 ln[2] = {s_ln[wg * 64 + rl], s_ln[wg * 64 + rl + 8]};
        epi_qkv_all(acc, smem + wg * (12 * 3072), s_cs, ln, args.qkv, nt, mt * 16 + wg * 8, rl, t, warp & 3
        );
    }
}

constexpr int WOPRE = 1, LAG = 3;
struct ChainArgs {
    const uint8_t *wo, *w1, *w2, *wqkv;
    const uint8_t *o, *xin;
    uint8_t *x1, *h, *x2;
    float2 *stats1, *stats2;
    const float *cs_w1, *cs_qkv, *vscale;
    uint8_t* qkv;
    unsigned* cnt;
    unsigned* flags;
    int do_qkv, kid;
};
constexpr int CH_NA = 5, CH_NB = 4, CH_BSLOT = 30720;
constexpr int CH_OFF_B = 2 * CH_NA * 8192, CH_OFF_X = CH_OFF_B + CH_NB * CH_BSLOT, CH_OFF_AUX = CH_OFF_X + 20480;
constexpr int CH_OFF_ST = CH_OFF_AUX + 2 * 128 * 8 + (216 + 240 + 240) * 4, CH_OFF_BAR = CH_OFF_ST + 128 * 8;
constexpr int CH_SMEM = CH_OFF_BAR + 8 * (4 * CH_NA + 2 * CH_NB + 8 + 20);

struct Ring { int s; uint32_t ph; };
template <int N> __device__ __forceinline__ void ring_next(Ring& r) { if (++r.s == N) { r.s = 0; r.ph ^= 1; } }

template <int BN, int KB, int KPS, int TAIL>
__device__ __forceinline__ void chain_mma(float (&acc)[BN / 2], Ring& ra, Ring& rb, uint32_t sA, uint32_t sB, uint32_t fullA, uint32_t emptyA,
                                          uint32_t fullB, uint32_t emptyB, int relA, int relB, int wtid, uint32_t prog = 0, int wg = 0) {
    const uint64_t dA0 = mk_desc(sA, 1024, 128, 0), dB0 = mk_desc(sB, 128, 1024, 0);
    if (BN != 80) {
#pragma unroll
        for (int i = 0; i < BN / 2; i++) acc[i] = 0.0f;
    }
    fence_regs(acc);
    uint32_t ea_r;
    asm("mapa.shared::cluster.u32 %0, %1, %2;" : "=r"(ea_r) : "r"(emptyA), "r"(wtid & 1));
    int pa = 0, pb = 0, nb = 0;
    bool okA = false, okB = false;
    int kb0 = 0;
#pragma unroll 1
    do {
        if (!okB) mbar_wait(fullB + 8 * rb.s, rb.ph);
        const uint64_t dB = dB0 + (uint64_t)(uint32_t)(rb.s * (CH_BSLOT >> 4));
        Ring nbr = rb; ring_next<CH_NB>(nbr);
#pragma unroll
        for (int kin = 0; kin < KPS; kin++) {
            const int kb = kb0 + kin;
            if (KB % KPS != 0 && kin > 0 && kb >= KB) break;
            if (!okA) mbar_wait(fullA + 8 * ra.s, ra.ph);
            if (TAIL > 0 && wg == 1 && kb == KB - TAIL) mbar_wait(prog, 0);
            const uint64_t dA = dA0 + (uint64_t)(uint32_t)(ra.s * 512);
            Ring nar = ra; ring_next<CH_NA>(nar);
            okA = mbar_test(fullA + 8 * nar.s, nar.ph);
            if (kin == KPS - 1) okB = mbar_test(fullB + 8 * nbr.s, nbr.ph);
            wg_fence();
#pragma unroll
            for (int k = 0; k < 4; k++) Mma<BN>::run(acc, dA + 128 * k, dB + kin * (BN * 8) + 16 * k);
            wg_commit();
            if (TAIL > 0 && wg == 0 && wtid == 0 && kb == KB - 1) mbar_arrive(prog);
            if (kb > 0) {
                wg_wait<1>();
                if (wtid < 2) {
                    if (kb - 1 < relA) asm volatile("mbarrier.arrive.shared::cluster.b64 _, [%0];" :: "r"(ea_r + 8 * pa) : "memory");
                    if (kin == 0 && nb <= relB && wtid == 0) mbar_arrive(emptyB + 8 * pb);
                }
            }
            pa = ra.s; ra = nar;
        }
        pb = rb.s; rb = nbr; nb++;
        kb0 += KPS;
    } while (kb0 < KB);
    wg_wait<0>();
    fence_regs(acc);
    if (wtid < 2) {
        if (KB - 1 < relA) asm volatile("mbarrier.arrive.shared::cluster.b64 _, [%0];" :: "r"(ea_r + 8 * pa) : "memory");
        if (nb <= relB && wtid == 0) mbar_arrive(emptyB + 8 * pb);
    }
}

__global__ void __cluster_dims__(2, 1, 1) __launch_bounds__(384, 1)
chain_kernel(const __grid_constant__ CUtensorMap mapX  , const ChainArgs args) {
    extern __shared__ __align__(1024) uint8_t smem[];
    const uint32_t sbase = smem_u32(smem);
    float2* s_ln = reinterpret_cast<float2*>(smem + CH_OFF_AUX);
    float* s_cs1 = reinterpret_cast<float*>(s_ln + 256);
    float* s_csq = s_cs1 + 216;
    float* s_vs = s_csq + 240;
    const uint32_t fullA = sbase + CH_OFF_BAR, emptyA = fullA + 16 * CH_NA, fullB = emptyA + 16 * CH_NA, emptyB = fullB + 8 * CH_NB;
    const uint32_t barX = emptyB + 8 * CH_NB, barLn = barX + 8;
    const int tid = threadIdx.x, warp = __shfl_sync(0xffffffffu, tid >> 5, 0), lane = tid & 31;
    const int rank = blockIdx.x & 1;
    const int mtn = blockIdx.x >> 3, ntn = blockIdx.x & 7;
    const int totA = args.do_qkv ? 57 : 47;
    if (warp == 8) {
        if (elect_one()) {
#pragma unroll
            for (int s = 0; s < 2 * CH_NA; s++) { mbar_init(fullA + 8 * s, 1); mbar_init(emptyA + 8 * s, 2); }
#pragma unroll
            for (int s = 0; s < CH_NB; s++) { mbar_init(fullB + 8 * s, 1); mbar_init(emptyB + 8 * s, 2); }
#pragma unroll
            for (int s = 0; s < 12; s++) mbar_init(barX + 8 * s, 1);
            asm volatile("fence.mbarrier_init.release.cluster;" ::: "memory");
        }
        __syncwarp();
    }
    auto wo_slot = [&](int s) {
        const int n = s < 3 ? 3 : 1;
        mbar_expect_tx(fullB + 8 * s, n * 10240);
        for (int j = 0; j < n; j++)
            bulk_g2s(sbase + CH_OFF_B + s * CH_BSLOT + j * 10240, args.wo + (size_t)((3 * s + j) * 80 + ntn * 10) * 1024, 10240, fullB + 8 * s);
    };
    cluster_arrive_relaxed();
    if (warp == 8) {
        if (args.do_qkv) flag_wait(args.cnt + CNT_RETILE, 256);
        __syncwarp();
        if (elect_one()) {
            asm volatile("fence.proxy.async.global;" ::: "memory");
            mbar_expect_tx(barX, 20480);
            for (int j = 0; j < 2; j++) {
                if (args.do_qkv) tma_2d(sbase + CH_OFF_X + j * 10240, &mapX, ntn * 80, mtn * 128 + j * 64, barX);
                else bulk_g2s(sbase + CH_OFF_X + j * 10240, args.xin + (size_t)((mtn * 2 + j) * 80 + ntn * 10) * 1024, 10240, barX);
            }
#pragma unroll 1
            for (int s = 0; s < WOPRE; s++) wo_slot(s);
            if (!args.do_qkv) prefetch_map(&mapX);
        }
        __syncwarp();
    }
    cluster_wait();

    if (warp == 8) {
#pragma unroll 1
        for (int s = WOPRE; s < 4; s++) {
            mbar_wait(fullB + 8 * (s - WOPRE), 0);
            if (elect_one()) wo_slot(s);
            __syncwarp();
        }
        if (elect_one()) {
            Ring r = {0, 0};
            int use = CH_NB;
            auto narrow = [&](const uint8_t* w, int KB) {
#pragma unroll 1
                for (int kb = 0; kb < KB; kb += 3, use++) {
                    const int n = KB - kb < 3 ? KB - kb : 3;
                    if (use >= CH_NB) mbar_wait(emptyB + 8 * r.s, r.ph);
                    mbar_expect_tx(fullB + 8 * r.s, n * 10240);
                    for (int j = 0; j < n; j++)
                        bulk_g2s(sbase + CH_OFF_B + r.s * CH_BSLOT + j * 10240, w + (size_t)((kb + j) * 80 + ntn * 10) * 1024, 10240, fullB + 8 * r.s);
                    ring_next<CH_NB>(r);
                }
            };
            auto wide = [&](const uint8_t* w, int chunks  ) {
#pragma unroll 1
                for (int kb = 0; kb < 10; kb++, use++) {
                    mbar_wait(emptyB + 8 * r.s, r.ph);
                    mbar_expect_tx(fullB + 8 * r.s, chunks * 1024);
                    bulk_g2s(sbase + CH_OFF_B + r.s * CH_BSLOT, w + (size_t)(kb * 8 + ntn) * chunks * 1024, chunks * 1024, fullB + 8 * r.s);
                    ring_next<CH_NB>(r);
                }
            };
            wide(args.w1, 27);
            pdl_wait();
            narrow(args.w2, 27);
            if (args.do_qkv) wide(args.wqkv, 30);
        }
        __syncwarp();
        pdl_wait();
    } else if (warp == 11) {
        {
            float4 s[2], q[2], v[2];
#pragma unroll
            for (int i = 0; i < 2; i++) {
                const int j = 4 * (lane + 32 * i);
                s[i] = make_float4(0.f, 0.f, 0.f, 0.f); q[i] = s[i]; v[i] = make_float4(1.f, 1.f, 1.f, 1.f);
                if (j < 216) {
#pragma unroll
                    for (int p = 0; p < 8; p++) {
                        const float4 a = __ldg(reinterpret_cast<const float4*>(args.cs_w1 + p * FF + ntn * 216 + j));
                        s[i].x += a.x; s[i].y += a.y; s[i].z += a.z; s[i].w += a.w;
                    }
                }
                if (j < 240 && args.do_qkv) {
                    q[i] = __ldg(reinterpret_cast<const float4*>(args.cs_qkv + ntn * 240 + j));
                    if (ntn * 240 + j >= 2 * DM) v[i] = __ldg(reinterpret_cast<const float4*>(args.vscale + ntn * 240 + j - 2 * DM));
                }
            }
#pragma unroll
            for (int i = 0; i < 2; i++) {
                const int j = 4 * (lane + 32 * i);
                if (j < 216) *reinterpret_cast<float4*>(s_cs1 + j) = s[i];
                if (j < 240) { *reinterpret_cast<float4*>(s_csq + j) = q[i]; *reinterpret_cast<float4*>(s_vs + j) = v[i]; }
            }
            __syncwarp();
            if (lane == 0) mbar_arrive(barLn + 32);
        }
        const float4* s_st = reinterpret_cast<const float4*>(smem + CH_OFF_ST);
#pragma unroll 1
        for (int p = 0; p < (args.do_qkv ? 2 : 1); p++) {
            float4* g = reinterpret_cast<float4*>((p ? args.stats2 : args.stats1) + ntn * SEQ + mtn * 128);
            named_bar_sync(4, 160);
            g[lane] = s_st[lane];
            named_bar_sync(5, 160);
            g[32 + lane] = s_st[32 + lane];
            __syncwarp();
            if (lane < 2) red_release_add(args.flags + (2 * p * 32 + mtn * 2 + lane) * CNT_STRIDE, 256);
            __syncwarp();
        }
    } else if (warp >= 9) {
        const int h = warp - 9;
        const uint32_t sA = sbase + h * (CH_NA * 8192), fA = fullA + 8 * CH_NA * h, eA = emptyA + 8 * CH_NA * h;
        Ring r = {0, 1};
        int use = 0;
        auto loads = [&](const uint8_t* src, int n) {
#pragma unroll 1
            for (int kb = 0; kb < n; kb++, use++) {
                if (use >= CH_NA) mbar_wait(eA + 8 * r.s, r.ph);
                if (elect_one()) {
                    mbar_expect_tx(fA + 8 * r.s, 8192);
                    if (rank == h) bulk_g2s_mc(sA + r.s * 8192, src + kb * 8192, 8192, fA + 8 * r.s, (uint16_t)3);
                }
                __syncwarp();
                ring_next<CH_NA>(r);
            }
        };
        auto stats = [&](const float2* st, int which) {
            float2 a[2][8];
#pragma unroll
            for (int i = 0; i < 2; i++)
#pragma unroll
                for (int j = 0; j < 8; j++) a[i][j] = __ldcg(st + j * SEQ + mtn * 128 + h * 64 + lane + 32 * i);
            s_ln[which * 128 + h * 64 + lane] = ln_combine(a[0]);
            s_ln[which * 128 + h * 64 + lane + 32] = ln_combine(a[1]);
            __syncwarp();
            if (lane == 0) mbar_arrive(barLn + 8 * (which * 2 + h));
        };
        pdl_wait();
        pdl_launch();
        loads(args.o + (size_t)(mtn * 2 + h) * 81920, 10);
        if (rank == h) {
            flag_wait(args.flags + (0 * 32 + mtn * 2 + h) * CNT_STRIDE, 8, 255);
            asm volatile("fence.proxy.async.global;" ::: "memory");
        }
        loads(args.x1 + (size_t)(mtn * 2 + h) * 81920, 10);
        flag_wait(args.flags + (0 * 32 + mtn * 2 + h) * CNT_STRIDE, 8 * 256);
        stats(args.stats1, 0);
        if (rank == h) {
            flag_wait(args.flags + (1 * 32 + mtn * 2 + h) * CNT_STRIDE, 8);
            asm volatile("fence.proxy.async.global;" ::: "memory");
        }
        loads(args.h + (size_t)(mtn * 2 + h) * (216 * 1024), 27);
        if (args.do_qkv) {
            if (rank == h) {
                flag_wait(args.flags + (2 * 32 + mtn * 2 + h) * CNT_STRIDE, 8, 255);
                asm volatile("fence.proxy.async.global;" ::: "memory");
            }
            loads(args.x2 + (size_t)(mtn * 2 + h) * 81920, 10);
            flag_wait(args.flags + (2 * 32 + mtn * 2 + h) * CNT_STRIDE, 8 * 256);
            stats(args.stats2, 1);
        }
    } else {
        const int wg = warp >> 2, g = lane >> 2, t = lane & 3, wtid = tid & 127;
        const int rl = (warp & 3) * 16 + g;
        const uint32_t sA = sbase + wg * (CH_NA * 8192), sB = sbase + CH_OFF_B;
        const uint32_t fA = fullA + 8 * CH_NA * wg, eA = emptyA + 8 * CH_NA * wg;
        uint8_t* stg = smem + wg * (CH_NA * 8192);
        uint8_t* xw = smem + CH_OFF_X + wg * 10240;
        float2* s_st = reinterpret_cast<float2*>(smem + CH_OFF_ST) + wg * 64;
        Ring ra = {0, 0}, rb = {0, 0};
        {
            float acc[40];
            mbar_wait(barX, 0);
            if (args.do_qkv) res_init<160, 16>(acc, xw, rl, t);
            else res_init<16, 1024>(acc, xw, rl, t);
            chain_mma<80, 10, 3, 0>(acc, ra, rb, sA, sB, fA, eA, fullB, emptyB, 10, 4, wtid);
            epi_res_publish(acc, xw, s_st, args.x1 + (size_t)((mtn * 2 + wg) * 80 + ntn * 10) * 1024,
                            args.flags + (0 * 32 + mtn * 2 + wg) * CNT_STRIDE, rl, t, warp & 3, wg);
        }
        {
            float acc[108];
            chain_mma<216, 10, 1, LAG>(acc, ra, rb, sA, sB, fA, eA, fullB, emptyB, 10 - CH_NA, 10, wtid, barX + 64, wg);
            mbar_wait(barLn + 8 * wg, 0);
            mbar_wait(barLn + 32, 0);
            named_bar_sync(1 + wg, 128);
            const float2 ln[2] = {s_ln[wg * 64 + rl], s_ln[wg * 64 + rl + 8]};
            const uint32_t csa = opaque(smem_u32(s_cs1) + 8 * t);
            const float mul[2] = {0.5f * ln[0].y, 0.5f * ln[1].y};
#define SILU_PART(B0, B1)                                                                                             \
            ln_apply<108, B0, B1, false>(acc, csa, ln, mul); epi_silu<B0, B1>(acc, stg, rl, t);                       \
            fence_async_smem();                                                                                       \
            named_bar_sync(1 + wg, 128);                                                                              \
            if ((warp & 3) == 0 && elect_one()) { bulk_s2g(args.h + (size_t)((mtn * 2 + wg) * 216 + ntn * 27 + B0) * 1024, sA + B0 * 1024, (B1 - B0) * 1024); bulk_commit(); }
            SILU_PART(0, 4)
            SILU_PART(4, 11)
            SILU_PART(11, 19) SILU_PART(19, 27)
#undef SILU_PART
            if ((warp & 3) == 0 && elect_one()) {
                bulk_wait_all();
                red_release_add(args.flags + (1 * 32 + mtn * 2 + wg) * CNT_STRIDE, 1);
#pragma unroll
                for (int s = 0; s < CH_NA; s++) { mbar_arrive_cluster(eA + 8 * s, 0); mbar_arrive_cluster(eA + 8 * s, 1); }
            }
            __syncwarp();
        }
        {
            float acc[40];
            res_init<16, 1024>(acc, xw, rl, t);
            chain_mma<80, 27, 3, 0>(acc, ra, rb, sA, sB, fA, eA, fullB, emptyB, totA - 20 - CH_NA, args.do_qkv ? 9 : 9 - CH_NB, wtid);
            if (args.do_qkv) {
                epi_res_publish(acc, xw, s_st, args.x2 + (size_t)((mtn * 2 + wg) * 80 + ntn * 10) * 1024,
                                args.flags + (2 * 32 + mtn * 2 + wg) * CNT_STRIDE, rl, t, warp & 3, wg);
            } else {
                uint32_t x[20];
                epi_res<160, 16>(acc, xw, rl, t, x);
                fence_async_smem();
                named_bar_sync(1 + wg, 128);
                if ((warp & 3) == 0 && elect_one()) { tma_store_2d(&mapX, ntn * 80, mtn * 128 + wg * 64, smem_u32(xw)); bulk_commit(); bulk_wait_read(); }
                __syncwarp();
            }
        }
        if (args.do_qkv) {
            float acc[120];
            chain_mma<240, 10, 1, LAG>(acc, ra, rb, sA, sB, fA, eA, fullB, emptyB, 10 - CH_NA, 10 - CH_NB, wtid, barX + 72, wg);
            mbar_wait(barLn + 8 * (2 + wg), 0);
            named_bar_sync(1 + wg, 128);
            const float2 ln[2] = {s_ln[128 + wg * 64 + rl], s_ln[128 + wg * 64 + rl + 8]};
            epi_qkv_all(acc, stg, s_csq, ln, args.qkv, ntn, mtn * 16 + wg * 8, rl, t, warp & 3
            );
        }
    }
}

__device__ __align__(1024) uint8_t g_qkv[96 * HEAD_IMG];
__device__ __align__(1024) __nv_bfloat16 g_o[SEQ * DM];
__device__ __align__(1024) __nv_bfloat16 g_x[3][SEQ * DM];
__device__ __align__(1024) __nv_bfloat16 g_h[SEQ * FF];
__device__ __align__(1024) uint8_t g_wt[RETILE_UNITS * 8192];
__device__ __align__(256) float2 g_stats[3][SEQ * 8];
__device__ __align__(256) float2 g_ln0[SEQ];
__device__ __align__(256) float g_cs_qkv[3 * DM];
__device__ __align__(256) float g_cs_w1[8 * FF];
__device__ __align__(256) float g_psum[8 * 3 * DM];
__device__ __align__(256) float g_pmax[8 * DM];
__device__ __align__(256) float g_vscale[DM];
__device__ __align__(256) float g_vinv[DM];
__device__ __align__(256) unsigned g_cnt[CNT_TOTAL];

typedef CUresult (*EncodeFn)(CUtensorMap*, CUtensorMapDataType, cuuint32_t, void*, const cuuint64_t*, const cuuint64_t*,
                             const cuuint32_t*, const cuuint32_t*, CUtensorMapInterleave, CUtensorMapSwizzle,
                             CUtensorMapL2promotion, CUtensorMapFloatOOBfill);

static CUtensorMap make_map_2d(EncodeFn fn, const void* p, int cols, int rows, int bc, int br, bool swz) {
    CUtensorMap m;
    cuuint64_t dim[2] = {(cuuint64_t)cols, (cuuint64_t)rows}, str[1] = {(cuuint64_t)cols * 2};
    cuuint32_t box[2] = {(cuuint32_t)bc, (cuuint32_t)br}, es[2] = {1, 1};
    fn(&m, CU_TENSOR_MAP_DATA_TYPE_BFLOAT16, 2, const_cast<void*>(p), dim, str, box, es, CU_TENSOR_MAP_INTERLEAVE_NONE,
       swz ? CU_TENSOR_MAP_SWIZZLE_128B : CU_TENSOR_MAP_SWIZZLE_NONE, CU_TENSOR_MAP_L2_PROMOTION_L2_128B, CU_TENSOR_MAP_FLOAT_OOB_FILL_NONE);
    return m;
}
static CUtensorMap make_map_w(EncodeFn fn, const void* p, int K, int N, int bn) {
    CUtensorMap m;
    cuuint64_t dim[3] = {(cuuint64_t)bn, (cuuint64_t)(N / bn), (cuuint64_t)K}, str[2] = {(cuuint64_t)bn * 2, (cuuint64_t)N * 2};
    cuuint32_t box[3] = {64, 1, 64}, es[3] = {1, 1, 1};
    fn(&m, CU_TENSOR_MAP_DATA_TYPE_BFLOAT16, 3, const_cast<void*>(p), dim, str, box, es, CU_TENSOR_MAP_INTERLEAVE_NONE,
       CU_TENSOR_MAP_SWIZZLE_128B, CU_TENSOR_MAP_L2_PROMOTION_L2_128B, CU_TENSOR_MAP_FLOAT_OOB_FILL_NONE);
    return m;
}
static CUtensorMap make_map_rt(EncodeFn fn, const void* p, int K, int N, int nch = 8) {
    CUtensorMap m;
    cuuint64_t dim[3] = {8, (cuuint64_t)K, (cuuint64_t)(N / 8)}, str[2] = {(cuuint64_t)N * 2, 16};
    cuuint32_t box[3] = {8, 64, (cuuint32_t)nch}, es[3] = {1, 1, 1};
    fn(&m, CU_TENSOR_MAP_DATA_TYPE_BFLOAT16, 3, const_cast<void*>(p), dim, str, box, es, CU_TENSOR_MAP_INTERLEAVE_NONE,
       CU_TENSOR_MAP_SWIZZLE_NONE, CU_TENSOR_MAP_L2_PROMOTION_L2_128B, CU_TENSOR_MAP_FLOAT_OOB_FILL_NONE);
    return m;
}

template <typename... KArgs, typename... Args>
static void launch(void (*k)(KArgs...), int grid, int block, int smem, bool pdl, Args... args) {
    cudaLaunchConfig_t lc = {};
    lc.gridDim = dim3(grid); lc.blockDim = dim3(block); lc.dynamicSmemBytes = smem; lc.stream = cudaStreamPerThread;
    cudaLaunchAttribute at[1];
    at[0].id = cudaLaunchAttributeProgrammaticStreamSerialization; at[0].val.programmaticStreamSerializationAllowed = 1;
    lc.attrs = at; lc.numAttrs = pdl ? 1 : 0;
    cudaLaunchKernelEx(&lc, k, KArgs(args)...);
}

extern "C" void kernel_launch(void* const* d_in, const int* in_sizes, int n_in, void* d_out, int out_size) {
    const __nv_bfloat16* x0 = (const __nv_bfloat16*)d_in[0];
    const __nv_bfloat16* wqkv = (const __nv_bfloat16*)d_in[1];
    const __nv_bfloat16* wo = (const __nv_bfloat16*)d_in[2];
    const __nv_bfloat16* w1 = (const __nv_bfloat16*)d_in[4];
    const __nv_bfloat16* w2 = (const __nv_bfloat16*)d_in[5];

    void* fp = nullptr; cudaDriverEntryPointQueryResult qr;
    cudaGetDriverEntryPoint("cuTensorMapEncodeTiled", &fp, cudaEnableDefault, &qr);
    EncodeFn enc = (EncodeFn)fp;

    uint8_t *qkv, *wt; __nv_bfloat16 *o, *xs, *h; float2 *stats, *ln0; float *csq, *cs1, *vsc, *vin, *psum, *pmax; unsigned* cnt;
    cudaGetSymbolAddress((void**)&qkv, g_qkv); cudaGetSymbolAddress((void**)&o, g_o); cudaGetSymbolAddress((void**)&xs, g_x);
    cudaGetSymbolAddress((void**)&h, g_h); cudaGetSymbolAddress((void**)&stats, g_stats); cudaGetSymbolAddress((void**)&ln0, g_ln0);
    cudaGetSymbolAddress((void**)&csq, g_cs_qkv); cudaGetSymbolAddress((void**)&cs1, g_cs_w1);
    cudaGetSymbolAddress((void**)&vsc, g_vscale); cudaGetSymbolAddress((void**)&vin, g_vinv);
    cudaGetSymbolAddress((void**)&psum, g_psum); cudaGetSymbolAddress((void**)&pmax, g_pmax);
    cudaGetSymbolAddress((void**)&wt, g_wt); cudaGetSymbolAddress((void**)&cnt, g_cnt);

    cudaFuncSetAttribute(qkv1_kernel, cudaFuncAttributeMaxDynamicSharedMemorySize, Q1_SMEM);
    cudaFuncSetAttribute(chain_kernel, cudaFuncAttributeMaxDynamicSharedMemorySize, CH_SMEM);
    cudaFuncSetAttribute(attn_kernel, cudaFuncAttributeMaxDynamicSharedMemorySize, ATTN_SMEM);

    const CUtensorMap mXa = make_map_2d(enc, x0, DM, SEQ, 64, 64, true);
    const CUtensorMap mXr = make_map_2d(enc, x0, DM, SEQ, 80, 64, false), mOut = make_map_2d(enc, d_out, DM, SEQ, 80, 64, false);
    const CUtensorMap mWqkv = make_map_w(enc, wqkv, DM, 3 * DM, 240);
    RetileMaps rm;
    rm.m[0] = make_map_rt(enc, wo, DM, DM); rm.m[1] = make_map_rt(enc, w1, DM, FF);
    rm.m[2] = make_map_rt(enc, w2, FF, DM); rm.m[3] = make_map_rt(enc, wqkv, DM, 3 * DM);
    RetileArgs ra;
    ra.dst = wt; ra.cnt = cnt;

    Qkv1Args qa = {x0, wqkv, w1, ln0, csq, cs1, vsc, vin, psum, pmax, qkv, cnt, 1};
    launch(qkv1_kernel, 128, 384, Q1_SMEM, false, mXa, mWqkv, qa);
    for (int l = 0; l < 2; l++) {
        ra.enable = (l == 0);
        launch(attn_kernel, 128, ATTN_THREADS, ATTN_SMEM, true, (const uint8_t*)qkv, o, (const float*)vin, rm, ra, 2 + 5 * l);
        ChainArgs ca = {wt, wt + 100 * 8192, wt + 370 * 8192, wt + 640 * 8192, (const uint8_t*)o, (const uint8_t*)(xs + SEQ * DM),
                        (uint8_t*)(xs + 2 * l * SEQ * DM), (uint8_t*)h, (uint8_t*)(xs + SEQ * DM), stats + (2 * l) * SEQ * 8, stats + SEQ * 8, cs1, csq, vsc, qkv,
                        cnt, cnt + CNT_FLAGS + l * 96 * CNT_STRIDE, l == 0, 3 + 5 * l};
        launch(chain_kernel, 128, 384, CH_SMEM, true, l == 0 ? mXr : mOut, ca);
    }
}
```
